```python
import torch

def _softmax(x, axis=-1):
    return torch.softmax(x, dim=axis)
def _gelu(x):
    return torch.nn.functional.gelu(x, approximate="tanh")
def _silu(x):
    return torch.nn.functional.silu(x)
def _sigmoid(x):
    return torch.sigmoid(x)
def _layernorm(x, axis=-1, eps=1e-5):
    m = x.mean(dim=axis, keepdim=True)
    v = x.var(dim=axis, keepdim=True, unbiased=False)
    return (x - m) / torch.sqrt(v + eps)
def _scatter_add(tgt, idx, src, axis=0):
    return tgt.clone().index_add_(axis, idx, src)
def _segment_sum(src, seg, n):
    out = torch.zeros((n,) + src.shape[1:], dtype=src.dtype)
    return out.index_add_(0, seg, src)
def _pad(x, pw):
    flat = tuple(v for pair in reversed(pw) for v in pair)
    return torch.nn.functional.pad(x, flat)

kernel_name = 'standalone__deep_cross_wide_deep__recsys'

def setup_inputs():

    _w = (lambda a: (lambda t: t.to(torch.bfloat16) if t.is_floating_point() else t)(torch.as_tensor(a)))
    B, F, D = 4096, 26, 128
    V, Nd = min(1000, 100000), 13
    Din = F * D
    H = 4 * D
    return {
        "idx": _w((lambda lo, hi, *s: torch.randint(lo, hi, s))(0, V, B, F).to(torch.int64)),
        "table": _w((lambda *s: torch.randn(*s, dtype=torch.bfloat16) * 1.6)(V, D) * 0.05),
        "x_wide": _w((lambda *s: torch.randn(*s, dtype=torch.bfloat16) * 1.6)(B, Nd)),
        "w_wide": _w((lambda *s: torch.randn(*s, dtype=torch.bfloat16) * 1.6)(Nd) * 0.05),
        "b_wide": _w((lambda *s: torch.randn(*s, dtype=torch.bfloat16) * 1.6)(1) * 0.01),
        "W1": _w((lambda *s: torch.randn(*s, dtype=torch.bfloat16) * 1.6)(Din, H) * (2.0 / Din) ** 0.5),
        "b1": _w((lambda *s: torch.randn(*s, dtype=torch.bfloat16) * 1.6)(H) * 0.01),
        "W2": _w((lambda *s: torch.randn(*s, dtype=torch.bfloat16) * 1.6)(H) * (1.0 / H) ** 0.5),
        "b2": _w((lambda *s: torch.randn(*s, dtype=torch.bfloat16) * 1.6)(1) * 0.01),
    }

def reference(idx, table, x_wide, w_wide, b_wide, W1, b1, W2, b2):
    emb = table[idx]
    deep_in = emb.reshape(emb.shape[0], -1)
    h = deep_in @ W1 + b1
    h = h * (lambda x, dt: x.to(dt))(h > 0, h.dtype)
    deep_logit = h @ W2 + b2
    wide_logit = x_wide @ w_wide + b_wide
    return _sigmoid(wide_logit + deep_logit)
```

```cpp
#include <cuda_runtime.h>
#include <cuda_bf16.h>
#include <cuda.h>
#include <stdint.h>

#define APOS 0
#define TPROMO CU_TENSOR_MAP_L2_PROMOTION_L2_128B
#define WPROMO CU_TENSOR_MAP_L2_PROMOTION_L2_128B
#define XMODE 0
namespace {

constexpr int NF = 26, ND = 128, NV = 1000, NH = 512, NW = 13;
constexpr int NTHREADS = 384;
constexpr uint32_t SBASE = 1024;
constexpr uint32_t OFF_A = 8 * 128;
constexpr uint32_t OFF_W = 824 * 128;
constexpr uint32_t OFF_MISC = 1032 * 128;
constexpr uint32_t OFF_B = 1056 * 128;
constexpr int SMEM_BYTES = 232448;
constexpr uint32_t BAR_W = OFF_MISC;
constexpr uint32_t BAR_T = OFF_MISC + 64;
constexpr uint32_t BAR_FREE = OFF_MISC + 112;
constexpr uint32_t BAR_DONE = OFF_MISC + 120;
constexpr uint32_t BAR_X = OFF_MISC + 2432;
constexpr uint32_t BAR_I = OFF_MISC + 2496;
constexpr uint32_t OFF_IDX = OFF_A + 768 * 128;
constexpr uint32_t OFF_PAR = OFF_MISC + 128;
constexpr uint32_t OFF_WIDE = OFF_MISC + 2304;
constexpr uint32_t OFF_RED = OFF_MISC + 256;
constexpr uint32_t OFF_Z = OFF_B - 128;
constexpr int SPIN_LIMIT = 1 << 22;

struct Scratch {
    uint4 part[64][2][64][32];
    uint4 logit[128][64][8];
    uint4 idx4[2][128][32];
    uint2 idx2[2][128][32];
    uint32_t epoch, pad[3];
};
__device__ Scratch g_scratch;
#define STAMP(i) do {} while (0)

__device__ __forceinline__ void mbar_init(uint32_t bar, int cnt) {
    asm volatile("mbarrier.init.shared::cta.b64 [%0], %1;" ::"r"(bar), "r"(cnt) : "memory");
}
__device__ __forceinline__ void mbar_expect(uint32_t bar, int bytes) {
    asm volatile("mbarrier.arrive.expect_tx.shared::cta.b64 _, [%0], %1;" ::"r"(bar), "r"(bytes) : "memory");
}
__device__ __forceinline__ void mbar_arrive(uint32_t bar) {
    asm volatile("mbarrier.arrive.shared::cta.b64 _, [%0];" ::"r"(bar) : "memory");
}
__device__ __forceinline__ void fault() { asm volatile("st.global.u32 [%0], %1;" ::"l"(0ull), "r"(0) : "memory"); }
__device__ __forceinline__ void mbar_wait(uint32_t bar) {
    asm volatile(
        "{\n"
        ".reg .pred p;\n"
        ".reg .u32 n;\n"
        "mov.u32 n, 0;\n"
        "LW_%=:\n"
        "mbarrier.try_wait.parity.shared::cta.b64 p, [%0], 0;\n"
        "@p bra LD_%=;\n"
        "add.u32 n, n, 1;\n"
        "setp.gt.u32 p, n, 4194304;\n"
        "@p st.global.u32 [%1], n;\n"
        "bra LW_%=;\n"
        "LD_%=:\n"
        "}\n" ::"r"(bar), "l"(0ull) : "memory");
}
__device__ __forceinline__ void tma2d(uint32_t dst, const CUtensorMap* tm, uint32_t bar, int c0, int c1) {
    asm volatile("cp.async.bulk.tensor.2d.shared::cluster.global.mbarrier::complete_tx::bytes [%0], [%1, {%3, %4}], [%2];"
                 ::"r"(dst), "l"(tm), "r"(bar), "r"(c0), "r"(c1) : "memory");
}
__device__ __forceinline__ void tma3d(uint32_t dst, const CUtensorMap* tm, uint32_t bar, int c0, int c1, int c2) {
    asm volatile("cp.async.bulk.tensor.3d.shared::cluster.global.mbarrier::complete_tx::bytes [%0], [%1, {%3, %4, %5}], [%2];"
                 ::"r"(dst), "l"(tm), "r"(bar), "r"(c0), "r"(c1), "r"(c2) : "memory");
}
__device__ __forceinline__ void bulk_g2s(uint32_t dst, const void* src, int bytes, uint32_t bar) {
    asm volatile("cp.async.bulk.shared::cluster.global.mbarrier::complete_tx::bytes [%0], [%1], %2, [%3];"
                 ::"r"(dst), "l"(src), "r"(bytes), "r"(bar) : "memory");
}
__device__ __forceinline__ uint32_t lds32(uint32_t addr) {
    uint32_t v;
    asm volatile("ld.shared.b32 %0, [%1];" : "=r"(v) : "r"(addr) : "memory");
    return v;
}
__device__ __forceinline__ uint64_t desc_a(uint32_t addr) {
    return (uint64_t)(addr >> 4) | ((uint64_t)1 << 16) | ((uint64_t)64 << 32) | ((uint64_t)1 << 62);
}
__device__ __forceinline__ uint64_t desc_w(uint32_t addr) {
    return (uint64_t)(addr >> 4) | ((uint64_t)8 << 16) | ((uint64_t)16 << 32);
}
#define R4(i) "+f"(d[i]), "+f"(d[i + 1]), "+f"(d[i + 2]), "+f"(d[i + 3])
template <int SCALE_D>
__device__ __forceinline__ void wgmma104(float (&d)[52], uint64_t da, uint64_t db) {
    asm volatile(
        "wgmma.mma_async.sync.aligned.m64n104k16.f32.bf16.bf16 "
        "{%0,%1,%2,%3,%4,%5,%6,%7,%8,%9,%10,%11,%12,%13,%14,%15,%16,%17,%18,%19,%20,%21,%22,%23,%24,%25,"
        "%26,%27,%28,%29,%30,%31,%32,%33,%34,%35,%36,%37,%38,%39,%40,%41,%42,%43,%44,%45,%46,%47,%48,%49,%50,%51}, "
        "%52, %53, %54, 1, 1, 0, 1;"
        : R4(0), R4(4), R4(8), R4(12), R4(16), R4(20), R4(24), R4(28), R4(32), R4(36), R4(40), R4(44), R4(48)
        : "l"(da), "l"(db), "n"(SCALE_D));
}
__device__ __forceinline__ void wg_fence() { asm volatile("wgmma.fence.sync.aligned;" ::: "memory"); }
__device__ __forceinline__ void wg_commit() { asm volatile("wgmma.commit_group.sync.aligned;" ::: "memory"); }
template <int N> __device__ __forceinline__ void wg_wait() { asm volatile("wgmma.wait_group.sync.aligned %0;" ::"n"(N) : "memory"); }

__device__ __forceinline__ uint32_t pack_bf16(float lo, float hi) {
    uint32_t r;
    asm("cvt.rn.bf16x2.f32 %0, %1, %2;" : "=r"(r) : "f"(hi), "f"(lo));
    return r;
}
__device__ __forceinline__ void cswap_alu(uint32_t& a, uint32_t& b, bool p) { const uint32_t x = a, y = b; a = p ? y : x; b = p ? x : y; }
__device__ __forceinline__ void cswap_fma(uint32_t& a, uint32_t& b, uint32_t p, float one) {
    asm("{\n.reg .pred q;\n.reg .f32 t;\nsetp.ne.u32 q, %2, 0;\nmul.f32 t, %0, %3;\n@q mul.f32 %0, %1, %3;\n@q mul.f32 %1, t, %3;\n}\n"
        : "+f"(*reinterpret_cast<float*>(&a)), "+f"(*reinterpret_cast<float*>(&b)) : "r"(p), "f"(one));
}
__device__ __forceinline__ void cswap4(uint32_t (&a)[4], uint32_t (&b)[4], uint32_t p, float one) {
    cswap_fma(a[0], b[0], p, one); cswap_alu(a[1], b[1], p); cswap_fma(a[2], b[2], p, one); cswap_fma(a[3], b[3], p, one);
}
__device__ __forceinline__ void sts128(uint32_t addr, const uint32_t (&r)[4]) {
    asm volatile("st.shared.v4.b32 [%0], {%1,%2,%3,%4};" ::"r"(addr), "r"(r[0]), "r"(r[1]), "r"(r[2]), "r"(r[3]) : "memory");
}
__device__ __forceinline__ void use_now(const uint32_t (&r)[4], float one) {
    asm volatile("{\n.reg .pred p;\nsetp.eq.f32 p, %4, 0f00000000;\n@p st.volatile.shared.v4.b32 [%5], {%0,%1,%2,%3};\n}\n"
                 ::"r"(r[0]), "r"(r[1]), "r"(r[2]), "r"(r[3]), "f"(one), "r"(OFF_MISC));
}
__device__ __forceinline__ void stage_break(float one) {
    asm volatile("{\n.reg .pred p;\n.reg .f32 t;\nsetp.neu.f32 p, %0, 0f00000000;\n@p bra.uni LE_%=;\n"
                 "LB_%=:\nld.volatile.shared.f32 t, [%1];\nsetp.eq.f32 p, t, 0f00000000;\n@p bra.uni LB_%=;\nLE_%=:\n}\n" ::"f"(one), "r"(OFF_MISC) : "memory");
}
__device__ __forceinline__ void stm4(uint32_t addr, uint32_t a, uint32_t b, uint32_t c, uint32_t d) {
    asm volatile("stmatrix.sync.aligned.m8n8.x4.shared.b16 [%0], {%1,%2,%3,%4};" ::"r"(addr), "r"(a), "r"(b), "r"(c), "r"(d) : "memory");
}
__device__ __forceinline__ uint4 lds128(uint32_t addr) {
    uint4 v;
    asm volatile("ld.volatile.shared.v4.b32 {%0,%1,%2,%3}, [%4];" : "=r"(v.x), "=r"(v.y), "=r"(v.z), "=r"(v.w) : "r"(addr));
    return v;
}
__device__ __forceinline__ uint4 lds128_b(uint32_t rel) {
    uint4 v;
    asm volatile("ld.volatile.shared.v4.b32 {%0,%1,%2,%3}, [%4+135040];" : "=r"(v.x), "=r"(v.y), "=r"(v.z), "=r"(v.w) : "r"(rel));
    return v;
}
static_assert(OFF_Z == 135040, "immediate above");
__device__ __forceinline__ void mma_sel(float (&d)[4], const uint4& a, uint32_t b0, uint32_t b1) {
    asm volatile("mma.sync.aligned.m16n8k16.row.col.f32.bf16.bf16.f32 {%0,%1,%2,%3}, {%4,%5,%6,%7}, {%8,%9}, {%0,%1,%2,%3};"
                 : "+f"(d[0]), "+f"(d[1]), "+f"(d[2]), "+f"(d[3]) : "r"(a.x), "r"(a.y), "r"(a.z), "r"(a.w), "r"(b0), "r"(b1));
}
__device__ __forceinline__ uint4 ldg_rlx4(const void* p) {
    uint4 v;
    asm volatile("{\n.reg .b128 t;\nld.relaxed.gpu.global.b128 t, [%4];\nmov.b128 {%0,%1,%2,%3}, t;\n}\n"
                 : "=r"(v.x), "=r"(v.y), "=r"(v.z), "=r"(v.w) : "l"(p) : "memory");
    return v;
}
__device__ __forceinline__ uint4 ldg_rlx4v(const void* p) {
    uint4 v;
    asm volatile("ld.relaxed.gpu.global.v4.b32 {%0,%1,%2,%3}, [%4];" : "=r"(v.x), "=r"(v.y), "=r"(v.z), "=r"(v.w) : "l"(p) : "memory");
    return v;
}
__device__ __forceinline__ uint2 ldg_rlx2(const void* p) {
    uint2 v;
    asm volatile("{\n.reg .b64 t;\nld.relaxed.gpu.global.b64 t, [%2];\nmov.b64 {%0,%1}, t;\n}\n" : "=r"(v.x), "=r"(v.y) : "l"(p) : "memory");
    return v;
}
__device__ __forceinline__ uint32_t ldg_rlx1(const void* p) {
    uint32_t v;
    asm volatile("ld.relaxed.gpu.global.b32 %0, [%1];" : "=r"(v) : "l"(p) : "memory");
    return v;
}
__device__ __forceinline__ void stg_rlx4(void* p, uint4 v) {
    asm volatile("{\n.reg .b128 t;\nmov.b128 t, {%1,%2,%3,%4};\nst.relaxed.gpu.global.b128 [%0], t;\n}\n"
                 ::"l"(p), "r"(v.x), "r"(v.y), "r"(v.z), "r"(v.w) : "memory");
}
__device__ __forceinline__ void stg_rlx2(void* p, uint2 v) {
    asm volatile("{\n.reg .b64 t;\nmov.b64 t, {%1,%2};\nst.relaxed.gpu.global.b64 [%0], t;\n}\n" ::"l"(p), "r"(v.x), "r"(v.y) : "memory");
}
__device__ __forceinline__ void stg_rlx1(void* p, uint32_t v) {
    asm volatile("st.relaxed.gpu.global.b32 [%0], %1;" ::"l"(p), "r"(v) : "memory");
}
__device__ __forceinline__ void pin_acc(float (&d)[52]) {
#pragma unroll
    for (int i = 0; i < 52; i++) asm volatile("" : "+f"(d[i])::"memory");
}
__device__ __forceinline__ float ldg_bf16(const void* p) {
    uint16_t v;
    asm volatile("ld.global.nc.u16 %0, [%1];" : "=h"(v) : "l"(p));
    return __uint_as_float((uint32_t)v << 16);
}

struct Codes { uint32_t w[6]; };
struct TrueT { static constexpr bool value = true; };
struct FalseT { static constexpr bool value = false; };
__host__ __device__ constexpr int posA(int i) { return i == 0 ? 39 : i == 1 ? 103 : i < 5 ? 95 + 10 * i : 97 + 10 * i; }
__host__ __device__ constexpr int posB(int i) { return i < 3 ? 13 * i : i < 7 ? 12 + 13 * i : 179; }
__device__ __forceinline__ uint32_t window(const Codes& c, const int pos, const int tgt) {
    const int wd = pos / 32, b = pos % 32;
    if (b == tgt) return c.w[wd];
    if (b < tgt) return c.w[wd] << (tgt - b);
    if (b + (17 - tgt) <= 32) return c.w[wd] >> (b - tgt);
    return __funnelshift_r(c.w[wd], c.w[(wd + 1) % 6], b - tgt);
}
__device__ __forceinline__ void put(Codes& c, const int pos, const int bits, uint32_t v) {
    const int wd = pos / 32, b = pos % 32;
    c.w[wd] |= v << b;
    if (b + bits > 32) c.w[(wd + 1) % 6] |= v >> (32 - b);
}
__device__ __forceinline__ void load_codes(Codes& c, uint64_t p4, uint64_t p2) {
    const uint4 a = ldg_rlx4(reinterpret_cast<const void*>(p4));
    const uint2 b = ldg_rlx2(reinterpret_cast<const void*>(p2));
    c.w[0] = a.x; c.w[1] = a.y; c.w[2] = a.z; c.w[3] = a.w; c.w[4] = b.x; c.w[5] = b.y;
}

__global__ void __cluster_dims__(2, 1, 1) __launch_bounds__(NTHREADS, 1)
wide_deep_kernel(Scratch* __restrict__ sc, const int* __restrict__ idx, const float one,
                 const __grid_constant__ CUtensorMap tmW, const __grid_constant__ CUtensorMap tmT,
                 const __nv_bfloat16* __restrict__ x_wide,
                 const __nv_bfloat16* __restrict__ w_wide, const __nv_bfloat16* __restrict__ b_wide,
                 const __nv_bfloat16* __restrict__ b1, const __nv_bfloat16* __restrict__ W2,
                 const __nv_bfloat16* __restrict__ b2, __nv_bfloat16* __restrict__ out) {
    extern __shared__ __align__(1024) unsigned char smem[];
    const int tid = threadIdx.x, lane = tid & 31;
    const int bid = blockIdx.x;
    const int h = (bid >> 1) & 1;
    const int cg = ((bid >> 2) << 1) | (bid & 1);
    const int g = lane >> 2, q = lane & 3;
    const uint32_t cwin = (uint32_t)__cvta_generic_to_shared(smem) - SBASE;

    if (tid == 0) STAMP(15);
    if (tid == 0) {
#pragma unroll
        for (int i = 0; i < 4; i++) mbar_init(cwin + BAR_W + 8 * i, 1);
        mbar_init(cwin + BAR_T, 1);
        mbar_init(cwin + BAR_I, 1);
        asm volatile("fence.mbarrier_init.release.cluster;" ::: "memory");
        mbar_expect(cwin + BAR_I, 32 * NF * 4 + 16);
        bulk_g2s(cwin + OFF_IDX, idx + bid * 32 * NF, 32 * NF * 4, cwin + BAR_I);
        bulk_g2s(cwin + OFF_IDX + 32 * NF * 4, &sc->epoch, 16, cwin + BAR_I);
#pragma unroll
        for (int ks = -1; ks < 4; ks++) {
            if (ks >= 0) {
                mbar_expect(cwin + BAR_W + 8 * ks, 3328);
                tma3d(cwin + OFF_W + ks * 3328, &tmW, cwin + BAR_W + 8 * ks, cg * 8, ks * 16, h * 13);
            }
            if (ks == APOS) {
                STAMP(14);
                mbar_expect(cwin + BAR_T, 32768);
                tma2d(cwin + OFF_A + 65536, &tmT, cwin + BAR_T, 0, 768);
            }
        }
    }
    const int warp = __shfl_sync(~0u, tid >> 5, 0);
    if (warp < 8) {
    if (warp == 0) asm volatile("bar.arrive 5, 160;" ::: "memory");
    asm volatile("bar.sync 1, 288;" ::: "memory");
    {
        if (warp == 4 || warp == 5) {
            const int hh = warp & 1;
            mbar_wait(cwin + BAR_I);
            const uint32_t tag = (lds32(cwin + OFF_IDX + 32 * NF * 4) & 1) ^ 1;
            const uint32_t ip = cwin + OFF_IDX + (4 * g * NF + hh * 13) * 4;
            uint32_t av[8], fv[4], ev;
#pragma unroll
            for (int gm = 0; gm < 4; gm++) {
                const uint32_t rp = ip + (((gm & 1) << 1) | (gm >> 1)) * NF * 4;
                av[2 * gm] = lds32(rp + (4 * (g & 1) + q) * 4);
                av[2 * gm + 1] = lds32(rp + (4 * ((g & 1) ^ 1) + q) * 4);
                fv[gm] = lds32(rp + (8 + q) * 4);
            }
            ev = lds32(ip + ((((q & 1) << 1) | (q >> 1)) * NF + 12) * 4);
            auto fix = [](uint32_t v) { v = ((int)v < 0) ? v + NV : v; return min(v, (uint32_t)(NV - 1)); };
#pragma unroll
            for (int i = 0; i < 8; i++) av[i] = fix(av[i]) + OFF_A / 128;
            ev = fix(ev);
            uint32_t bc[8];
            const uint32_t ebase = 8 + (ev < 768 ? (ev >> 4) * 128 + 64 : ((ev >> 4) - 16) * 128 + 96);
#pragma unroll
            for (int gm = 0; gm < 4; gm++) {
                const uint32_t v = fix(fv[gm]);
                const uint32_t fcode = 8 + q + (v < 768 ? (v >> 4) * 128 + (v & 15) * 4 : ((v >> 4) - 48 + ((v & 8) << 1)) * 128 + 96 + (v & 7) * 4);
                const uint32_t freeh = ~(__ballot_sync(~0u, v & 1) >> ((g ^ 1) << 2));
                const uint32_t cp = ((ev >> 2) ^ (freeh >> (ev & 3))) & 1;
                const uint32_t ecode = ebase + 16 * cp + ((ev & 15) ^ (cp << 2));
                const uint32_t zc = (__shfl_sync(~0u, ev, (lane & 28) + gm) + 1) & 3;
                const uint32_t zcode = zc + (((freeh >> zc) & 1) << 2);
                const uint32_t other = q == gm ? ecode : zcode;
                bc[2 * gm] = (g & 1) ? other : fcode;
                bc[2 * gm + 1] = (g & 1) ? fcode : other;
            }
            Codes c;
            c.w[0] = 0; c.w[1] = tag << 17; c.w[2] = 0; c.w[3] = 0; c.w[4] = tag << 17; c.w[5] = 0;
#pragma unroll
            for (int k = 0; k < 8; k++) { put(c, posA(k), 10, av[k]); put(c, posB(k), 13, bc[k]); }
            stg_rlx4(&sc->idx4[hh][bid][lane], make_uint4(c.w[0], c.w[1], c.w[2], c.w[3]));
            stg_rlx2(&sc->idx2[hh][bid][lane], make_uint2(c.w[4], c.w[5]));
        }
    }
    asm volatile("setmaxnreg.inc.sync.aligned.u32 240;");
    STAMP(0);

    const int wg = warp >> 2;
    uint32_t pkA[2][2][2][4], pkF[2][2][4], pkE[2][2];
    Codes cd[2][2];
    uint64_t pc4, pc2;
    const uint32_t slab = cwin + (uint32_t)(wg * 8 + (warp & 3)) * 2048;
    const uint32_t stA = OFF_A + slab + (uint32_t)g * 128 + (uint32_t)((g & 1) * 4 + q) * 16;
    {
        float acc[2][52];
        const uint64_t dw = desc_w(OFF_W);
        const uint64_t da0 = desc_a(OFF_A + 128 * wg * 128), da1 = desc_a(OFF_B + 128 * wg * 128);
        auto pack_entry = [](uint32_t (&e)[4], const float (&a)[52], const int i, const int rs) {
#pragma unroll
            for (int x = 0; x < 4; x++) e[x] = pack_bf16(a[16 * i + 4 * x + 2 * rs], a[16 * i + 4 * x + 2 * rs + 1]);
        };
        {
            float accp[2][52];
            mbar_wait(cwin + BAR_T);
#pragma unroll
            for (int ks = 0; ks < 4; ks++) {
                mbar_wait(cwin + BAR_W + 8 * ks);
                mbar_wait(cwin + BAR_X + 8 * ks);
                if (ks == 0) STAMP(1);
                wg_fence();
                if (ks == 0) { wgmma104<0>(accp[0], da0 + 4096, dw); wgmma104<0>(accp[1], da0 + 4096 + 512, dw); }
                else { wgmma104<1>(accp[0], da0 + 4096 + ks * 2, dw + ks * 208); wgmma104<1>(accp[1], da0 + 4096 + 512 + ks * 2, dw + ks * 208); }
            }
            mbar_wait(cwin + BAR_T + 32);
            wg_fence();
            wgmma104<0>(acc[0], da0, dw);
            wgmma104<0>(acc[1], da0 + 512, dw);
#pragma unroll
            for (int ks = 1; ks < 4; ks++) { wgmma104<1>(acc[0], da0 + ks * 2, dw + ks * 208); wgmma104<1>(acc[1], da0 + 512 + ks * 2, dw + ks * 208); }
            mbar_wait(cwin + BAR_T + 8);
#pragma unroll
            for (int ks = 4; ks < 8; ks++) {
                mbar_wait(cwin + BAR_W + 8 * ks);
                mbar_wait(cwin + BAR_X + 8 * ks);
                wg_fence();
                wgmma104<1>(accp[0], da1 + 4096 + (ks & 3) * 2, dw + ks * 208);
                wgmma104<1>(accp[1], da1 + 4096 + 512 + (ks & 3) * 2, dw + ks * 208);
            }
            wg_commit();
            mbar_wait(cwin + BAR_T + 40);
            wg_fence();
#pragma unroll
            for (int ks = 4; ks < 8; ks++) wgmma104<1>(acc[0], da1 + (ks & 3) * 2, dw + ks * 208);
            wg_commit();
            wg_wait<1>();
            if (lane == 0) mbar_arrive(cwin + BAR_FREE);
#pragma unroll
            for (int ks = 4; ks < 8; ks++) wgmma104<1>(acc[1], da1 + 512 + (ks & 3) * 2, dw + ks * 208);
            wg_commit();
            pin_acc(accp[0]);
            pin_acc(accp[1]);
            STAMP(2);
#pragma unroll
            for (int u = 0; u < 2; u++)
#pragma unroll
                for (int rs = 0; rs < 2; rs++) {
                    pack_entry(pkA[u][rs][0], accp[u], 0, rs);
                    pack_entry(pkA[u][rs][1], accp[u], 1, rs);
                    cswap4(pkA[u][rs][0], pkA[u][rs][1], g & 1, one);
                    pack_entry(pkF[u][rs], accp[u], 2, rs);
                    pkE[u][rs] = pack_bf16(accp[u][48 + 2 * rs], accp[u][49 + 2 * rs]);
                    use_now(pkA[u][rs][0], one);
                    use_now(pkA[u][rs][1], one);
                    use_now(pkF[u][rs], one);
                }
        }
        {
            const uint32_t t[4] = {pkE[0][0], pkE[0][1], pkE[1][0], pkE[1][1]};
            use_now(t, one);
        }
        const uint32_t stF = OFF_B + slab + (uint32_t)lane * 16;
        const uint32_t stE = OFF_B + slab + 1024 + (((uint32_t)lane * 16) ^ ((uint32_t)(lane >> 4) * 64));
        pc4 = reinterpret_cast<uint64_t>(&sc->idx4[h][(1 - h) * 64 + 2 * warp][lane]);
        pc2 = reinterpret_cast<uint64_t>(&sc->idx2[h][(1 - h) * 64 + 2 * warp][lane]);
        auto tile = [&](auto MMA, const int s, const int u) {
            constexpr bool mma = decltype(MMA)::value;
            uint32_t ea[2][2][4], ef[2][4], ee[2];
#pragma unroll
            for (int rs = 0; rs < 2; rs++) {
                pack_entry(ea[rs][0], acc[u], 0, rs);
                pack_entry(ea[rs][1], acc[u], 1, rs);
                pack_entry(ef[rs], acc[u], 2, rs);
                ee[rs] = pack_bf16(acc[u][48 + 2 * rs], acc[u][49 + 2 * rs]);
            }
            const uint64_t off = (uint64_t)(2048 * (s + 1) + 512 * u);
            auto H = [&](const int ks) { if (mma) wgmma104<1>(acc[u], (ks < 4 ? da0 : da1) + off + (ks & 3) * 2, dw + ks * 208); };
            if (mma) {
                if (u == 0) mbar_wait(cwin + BAR_T + 16 + 8 * s);
                wg_fence();
                wgmma104<0>(acc[u], da0 + off, dw);
            }
            asm volatile("bar.sync %0, 128;" ::"r"(2 + wg) : "memory");
            const uint32_t so = s * 32768 + u * 8192;
            sts128(stF + so, ef[0]);
            H(1);
            sts128(stF + so + 512, ef[1]);
            H(2);
            stm4(stE + so, ee[0], ee[1], ee[0], ee[1]);
            H(3);
            if (mma) {
                sts128(stF + so + 1536, pkF[u][0]);
#pragma unroll
                for (int x = 0; x < 4; x++) pkF[u][0][x] = pkF[u][1][x];
            } else {
                stm4(stE + so + 512, pkE[u][0], pkE[u][1], pkE[u][0], pkE[u][1]);
            }
            H(4);
            cswap4(ea[0][0], ea[0][1], g & 1, one);
            sts128(stA + so, ea[0][0]);
            H(5);
            sts128((stA + so) ^ 64, ea[0][1]);
            H(6);
            cswap4(ea[1][0], ea[1][1], g & 1, one);
            sts128(stA + so + 1024, ea[1][0]);
            H(7);
            if (mma) wg_commit();
            sts128((stA + so + 1024) ^ 64, ea[1][1]);
        };
#pragma unroll
        for (int s = 0; s < 2; s++) {
#pragma unroll
            for (int u = 0; u < 2; u++) {
                wg_wait<1>();
                pin_acc(acc[u]);
                if (u == 0) STAMP(3 + 2 * s);
                tile(TrueT{}, s, u);
                if (s == 1) {
                    load_codes(cd[u][0], pc4 + u * 16 * 512, pc2 + u * 16 * 256);
                    load_codes(cd[u][1], pc4 + u * 16 * 512 + 512, pc2 + u * 16 * 256 + 256);
                }
                if (u == 1) STAMP(4 + 2 * s);
            }
        }
        wg_wait<1>();
        pin_acc(acc[0]);
        STAMP(7);
        tile(FalseT{}, 2, 0);
        wg_wait<0>();
        pin_acc(acc[1]);
        if (lane == 0) mbar_arrive(cwin + BAR_DONE);
        tile(FalseT{}, 2, 1);
        STAMP(8);
    }
    mbar_wait(cwin + BAR_DONE);
#pragma unroll
    for (int u = 0; u < 2; u++)
#pragma unroll
        for (int rs = 0; rs < 2; rs++) {
            sts128(stA + 3 * 32768 + u * 8192 + rs * 1024, pkA[u][rs][0]);
            sts128((stA + 3 * 32768 + u * 8192 + rs * 1024) ^ 64, pkA[u][rs][1]);
        }
    uint32_t epoch;
    float bias[4], w2[4];
    asm volatile("ld.shared.b32 %0, [%1];" : "=r"(epoch) : "r"(cwin + OFF_PAR + 64) : "memory");
    asm volatile("ld.shared.v4.f32 {%0,%1,%2,%3}, [%4];" : "=f"(bias[0]), "=f"(bias[1]), "=f"(bias[2]), "=f"(bias[3]) : "r"(cwin + OFF_PAR + (q & 1) * 16) : "memory");
    asm volatile("ld.shared.v4.f32 {%0,%1,%2,%3}, [%4];" : "=f"(w2[0]), "=f"(w2[1]), "=f"(w2[2]), "=f"(w2[3]) : "r"(cwin + OFF_PAR + 32 + (q & 1) * 16) : "memory");
    uint32_t tag = (epoch & 1) ^ 1;
    uint32_t tag17 = tag << 17;
    uint32_t offA0 = cwin | ((uint32_t)(4 * (g & 1) + q) << 4), offA1 = cwin | ((uint32_t)(4 * ((g + 1) & 1) + q) << 4), offB = cwin;
    uint32_t sel[2][2];
#pragma unroll
    for (int u = 0; u < 2; u++) {
        sel[u][0] = g == 4 * u ? 0x3F80u : (g == 4 * u + 1 ? 0x3F800000u : 0u);
        sel[u][1] = g == 4 * u + 2 ? 0x3F80u : (g == 4 * u + 3 ? 0x3F800000u : 0u);
    }
    uint64_t ppart = reinterpret_cast<uint64_t>(&sc->part[cg][1 - h][2 * warp][lane]);
    uint64_t plog = reinterpret_cast<uint64_t>(reinterpret_cast<uint32_t*>(&sc->logit[h * 64 + 2 * warp][cg][0]) + lane);
    const int dhalf = 2 * h - 1;
    asm volatile("bar.sync 1, 256;" ::: "memory");
    STAMP(9);

    auto validate = [&](Codes (&c)[2], const uint64_t p4, const uint64_t p2) {
        auto stale = [&]() { return (((c[0].w[1] ^ tag17) | (c[0].w[4] ^ tag17) | (c[1].w[1] ^ tag17) | (c[1].w[4] ^ tag17)) & 0x20000u) != 0; };
        if (__any_sync(~0u, stale())) {
            int spins = 0;
            do {
                load_codes(c[0], p4, p2);
                load_codes(c[1], p4 + 512, p2 + 256);
                if (++spins > SPIN_LIMIT) fault();
            } while (__any_sync(~0u, stale()));
        }
    };
    uint4 va[2][8];
    float cinit[4] = {0.f, 0.f, 0.f, 0.f};
    auto load_a = [&](const Codes (&c)[2]) {
#pragma unroll
        for (int k = 0; k < 8; k++)
#pragma unroll
            for (int u = 0; u < 2; u++) {
                const int kk = (k >> 1) + (k & 1) * 4;
                va[u][kk] = lds128((window(c[u], posA(kk), 7) & 0x1FF80u) | ((kk & 1) ? offA1 : offA0));
            }
    };
    validate(cd[0], pc4, pc2);
    load_a(cd[0]);
#pragma unroll 1
    for (int own = 0; own < 2; own++) {
#pragma unroll
        for (int i = 0; i < 4; i++) {
            Codes(&c)[2] = cd[i & 1];
            const bool more = i < 3 || !own;
            const uint64_t n4 = i < 3 ? pc4 + (i + 1) * 16 * 512 : pc4 + dhalf * 64 * 512;
            const uint64_t n2 = i < 3 ? pc2 + (i + 1) * 16 * 256 : pc2 + dhalf * 64 * 256;
            uint4 vb[2][8];
#pragma unroll
            for (int k = 0; k < 4; k++)
#pragma unroll
                for (int u = 0; u < 2; u++) {
                    vb[u][k] = lds128_b((window(c[u], posB(k), 4) & 0x1FFF0u) | offB);
                    vb[u][k + 4] = lds128_b((window(c[u], posB(k + 4), 4) & 0x1FFF0u) | offB);
                }
            uint4 pin[2];
            if (own) {
#pragma unroll
                for (int u = 0; u < 2; u++) pin[u] = ldg_rlx4(reinterpret_cast<const void*>(ppart + (i * 16 + u) * 512));
            }
            if (more) validate(cd[(i + 1) & 1], n4, n2);
            float d[4][4];
#pragma unroll
            for (int s = 0; s < 4; s++)
#pragma unroll
                for (int k = 0; k < 4; k++) d[s][k] = cinit[k];
#pragma unroll
            for (int k = 0; k < 4; k++)
#pragma unroll
                for (int u = 0; u < 2; u++) {
                    mma_sel(d[2 * u], va[u][k], sel[k >> 1][0], sel[k >> 1][1]);
                    mma_sel(d[2 * u + 1], va[u][k + 4], sel[k >> 1][0], sel[k >> 1][1]);
                }
            if (more) load_a(cd[(i + 1) & 1]);
            if (i < 2) {
                load_codes(c[0], pc4 + (i + 2) * 16 * 512, pc2 + (i + 2) * 16 * 256);
                load_codes(c[1], pc4 + (i + 2) * 16 * 512 + 512, pc2 + (i + 2) * 16 * 256 + 256);
            } else if (!own) {
                load_codes(c[0], pc4 + dhalf * 64 * 512 + (i - 2) * 16 * 512, pc2 + dhalf * 64 * 256 + (i - 2) * 16 * 256);
                load_codes(c[1], pc4 + dhalf * 64 * 512 + (i - 2) * 16 * 512 + 512, pc2 + dhalf * 64 * 256 + (i - 2) * 16 * 256 + 256);
            }
            stage_break(one);
#pragma unroll
            for (int k = 0; k < 4; k++) {
#pragma unroll
                for (int u = 0; u < 2; u++) {
                    mma_sel(d[2 * u], vb[u][k], sel[k >> 1][0], sel[k >> 1][1]);
                    mma_sel(d[2 * u + 1], vb[u][k + 4], sel[k >> 1][0], sel[k >> 1][1]);
                }
            }
            if (!own) {
#pragma unroll
                for (int u = 0; u < 2; u++) {
                    const uint32_t x0 = ((__float_as_uint(d[2 * u][0]) + 0x10000u) & 0xFFFE0000u) | (tag << 16);
                    stg_rlx4(reinterpret_cast<void*>(ppart + (i * 16 + u) * 512),
                             make_uint4(pack_bf16(__uint_as_float(x0), d[2 * u][1]), pack_bf16(d[2 * u][2], d[2 * u][3]),
                                        pack_bf16(d[2 * u + 1][0], d[2 * u + 1][1]), pack_bf16(d[2 * u + 1][2], d[2 * u + 1][3])));
                }
            } else {
                pin[0].x ^= tag; pin[1].x ^= tag;
                if (__any_sync(~0u, ((pin[0].x | pin[1].x) & 1u) != 0)) {
                    int spins = 0;
                    do {
#pragma unroll
                        for (int u = 0; u < 2; u++) { pin[u] = ldg_rlx4(reinterpret_cast<const void*>(ppart + (i * 16 + u) * 512)); pin[u].x ^= tag; }
                        if (++spins > SPIN_LIMIT) fault();
                    } while (__any_sync(~0u, ((pin[0].x | pin[1].x) & 1u) != 0));
                }
                float t[4];
#pragma unroll
                for (int s = 0; s < 4; s++) {
                    const uint32_t p0 = (s & 1) ? pin[s >> 1].z : pin[s >> 1].x, p1 = (s & 1) ? pin[s >> 1].w : pin[s >> 1].y;
                    t[s] = fmaxf(d[s][0] + __uint_as_float(p0 << 16), 0.f) * w2[0];
                    t[s] = fmaf(fmaxf(d[s][1] + __uint_as_float(p0 & 0xFFFF0000u), 0.f), w2[1], t[s]);
                    t[s] = fmaf(fmaxf(d[s][2] + __uint_as_float(p1 << 16), 0.f), w2[2], t[s]);
                    t[s] = fmaf(fmaxf(d[s][3] + __uint_as_float(p1 & 0xFFFF0000u), 0.f), w2[3], t[s]);
                }
#pragma unroll
                for (int u = 0; u < 2; u++) {
                    const float keep = (q & 1) ? t[2 * u + 1] : t[2 * u], send = (q & 1) ? t[2 * u] : t[2 * u + 1];
                    const float res = keep + __shfl_xor_sync(~0u, send, 1);
                    stg_rlx1(reinterpret_cast<void*>(plog + (i * 16 + u) * 8192), (__float_as_uint(res) & ~1u) | tag);
                }
            }
        }
        if (!own) STAMP(13);
        ppart += (int64_t)dhalf * 32768;
        pc4 += (int64_t)dhalf * 64 * 512;
        pc2 += (int64_t)dhalf * 64 * 256;
#pragma unroll
        for (int k = 0; k < 4; k++) cinit[k] = bias[k];
    }
    STAMP(10);

    {
        const uint4* lp = &sc->logit[bid][0][0] + tid;
        uint4 v = ldg_rlx4v(lp), y = ldg_rlx4v(lp + 256);
        int spins = 0;
        while ((((v.x ^ tag) | (v.y ^ tag) | (v.z ^ tag) | (v.w ^ tag) | (y.x ^ tag) | (y.y ^ tag) | (y.z ^ tag) | (y.w ^ tag)) & 1u) != 0) {
            v = ldg_rlx4v(lp);
            y = ldg_rlx4v(lp + 256);
            if (++spins > SPIN_LIMIT) fault();
        }
        __syncwarp();
        STAMP(11);
        float s0 = __uint_as_float(v.x ^ tag) + __uint_as_float(y.x ^ tag), s1 = __uint_as_float(v.y ^ tag) + __uint_as_float(y.y ^ tag);
        float s2 = __uint_as_float(v.z ^ tag) + __uint_as_float(y.z ^ tag), s3 = __uint_as_float(v.w ^ tag) + __uint_as_float(y.w ^ tag);
#pragma unroll
        for (int o = 8; o < 32; o <<= 1) {
            s0 += __shfl_xor_sync(~0u, s0, o); s1 += __shfl_xor_sync(~0u, s1, o);
            s2 += __shfl_xor_sync(~0u, s2, o); s3 += __shfl_xor_sync(~0u, s3, o);
        }
        if (lane < 8)
            asm volatile("st.shared.v4.f32 [%0], {%1,%2,%3,%4};" ::"r"(cwin + OFF_RED + warp * 128 + lane * 16), "f"(s0), "f"(s1), "f"(s2), "f"(s3) : "memory");
        asm volatile("bar.sync 6, 288;" ::: "memory");
        if (warp == 0) {
            float z;
            asm volatile("ld.shared.f32 %0, [%1];" : "=f"(z) : "r"(cwin + OFF_WIDE + lane * 4) : "memory");
#pragma unroll
            for (int i = 0; i < 8; i++) {
                float x;
                asm volatile("ld.shared.f32 %0, [%1];" : "=f"(x) : "r"(cwin + OFF_RED + i * 128 + lane * 4) : "memory");
                z += x;
            }
            out[bid * 32 + lane] = __float2bfloat16(1.f / (1.f + __expf(-z)));
            if (bid == 0 && lane == 0) stg_rlx1(&sc->epoch, epoch + 1);
        }
        STAMP(12);
    }
    } else {
        asm volatile("setmaxnreg.dec.sync.aligned.u32 24;");
        if (warp != 8) {
            if (lane == 0) {
                if (warp == 9) {
#pragma unroll
                    for (int i = 4; i < 8; i++) mbar_init(cwin + BAR_W + 8 * i, 1);
                    mbar_init(cwin + BAR_FREE, 8);
                    mbar_init(cwin + BAR_DONE, 11);
                } else if (warp == 10) {
#pragma unroll
                    for (int i = 1; i < 6; i++) mbar_init(cwin + BAR_T + 8 * i, 1);
                } else {
#pragma unroll
                    for (int i = 0; i < 8; i++) mbar_init(cwin + BAR_X + 8 * i, XMODE == 0 ? 3 : 1);
                }
                asm volatile("fence.mbarrier_init.release.cluster;" ::: "memory");
            }
            __syncwarp();
            asm volatile("bar.sync 5, 160;" ::: "memory");
            const uint32_t xh = (lane >> 3) & 1;
            uint32_t x0 = cwin + OFF_W + (warp - 9) * 1024 + ((lane & 7) + (lane >> 4) * 8) * 16;
#pragma unroll 1
            for (int ks = 0; ks < 8; ks++, x0 += 3328) {
                mbar_wait(cwin + BAR_W + 8 * ks);
                STAMP(ks);
                uint32_t lo[4], hi[4];
#pragma unroll
                for (int x = 0; x < 4; x++)
                    asm volatile("ld.shared.v2.b32 {%0,%1}, [%2];" : "=r"(lo[x]), "=r"(hi[x]) : "r"(x0 + x * 256 + xh * 8) : "memory");
                __syncwarp();
                sts128(x0 + xh * 512, lo);
                sts128(x0 + xh * 512 + 256, hi);
                asm volatile("fence.proxy.async.shared::cta;" ::: "memory");
                __syncwarp();
                if (lane == 0) mbar_arrive(cwin + BAR_X + 8 * ks);
                STAMP(8 + ks);
            }
            const uint32_t stale = ldg_rlx1(&sc->epoch) & 1;
#pragma unroll 1
            for (int i = tid - 288; i < 512; i += 96) stg_rlx4(&sc->logit[h * 64 + (i >> 3)][cg][i & 7], make_uint4(stale, stale, stale, stale));
            if (warp == 9) {
                const uint32_t* pp = lane < 4 ? reinterpret_cast<const uint32_t*>(b1) + cg * 4 + lane
                                   : lane < 8 ? reinterpret_cast<const uint32_t*>(W2) + cg * 4 + lane - 4 : &sc->epoch;
                const uint32_t e = ldg_rlx1(pp);
                asm volatile("st.shared.b32 [%0], %1;" ::"r"(cwin + OFF_Z + lane * 4), "r"(0) : "memory");
                if (lane <= 8)
                    asm volatile("st.shared.v2.b32 [%0], {%1,%2};" ::"r"(cwin + OFF_PAR + lane * 8), "r"(lane < 8 ? e << 16 : e), "r"(e & 0xffff0000u) : "memory");
            }
            __syncwarp();
            if (lane == 0) mbar_arrive(cwin + BAR_DONE);
            if (warp == 10) {
                mbar_wait(cwin + BAR_DONE);
                const __nv_bfloat16* xp = x_wide + (bid * 32 + lane) * NW;
                const float wv = ldg_bf16(lane < NW ? w_wide + lane : (lane == NW ? b_wide : b2));
                float wide = __shfl_sync(~0u, wv, NW) + __shfl_sync(~0u, wv, NW + 1);
#pragma unroll 1
                for (int i = 0; i < NW; i++) wide = fmaf(ldg_bf16(xp + i), __shfl_sync(~0u, wv, i), wide);
                asm volatile("st.shared.f32 [%0], %1;" ::"r"(cwin + OFF_WIDE + lane * 4), "f"(wide) : "memory");
                asm volatile("bar.arrive 6, 288;" ::: "memory");
            }
        } else {
            asm volatile("bar.sync 5, 160;" ::: "memory");
            asm volatile("bar.arrive 1, 288;" ::: "memory");
            if (lane == 0) {
#pragma unroll 1
                for (int ks = 3; ks < 8; ks++) {
                    if (ks > 3) {
                        mbar_expect(cwin + BAR_W + 8 * ks, 3328);
                        tma3d(cwin + OFF_W + ks * 3328, &tmW, cwin + BAR_W + 8 * ks, cg * 8, ks * 16, h * 13);
                    }
                    STAMP(ks);
                    if ((0xA8 >> ks) & 1) {
                        const int hf = ks >> 2, first = ks == 5;
                        const uint32_t bar = cwin + BAR_T + 8 * hf + (first ? 0 : 32);
                        mbar_expect(bar, 32768);
                        tma2d(cwin + (hf ? OFF_B : OFF_A) + (first ? 65536 : 0), &tmT, bar, 64 * hf, first ? 768 : 0);
                        STAMP(8 + ks);
                    }
                }
                if ((cwin & 0xFFFFFFu) != 0) fault();
#pragma unroll 1
                for (int t = 1; t < 3; t++) {
                    if (t == 2) mbar_wait(cwin + BAR_FREE);
                    mbar_expect(cwin + BAR_T + 8 + 8 * t, 65536);
                    tma2d(cwin + OFF_A + 32768 * t, &tmT, cwin + BAR_T + 8 + 8 * t, 0, 256 * t);
                    tma2d(cwin + OFF_B + 32768 * t, &tmT, cwin + BAR_T + 8 + 8 * t, 64, 256 * t);
                }
            }
        }
    }
}

typedef CUresult (*EncodeFn)(CUtensorMap*, CUtensorMapDataType, cuuint32_t, void*, const cuuint64_t*, const cuuint64_t*,
                             const cuuint32_t*, const cuuint32_t*, CUtensorMapInterleave, CUtensorMapSwizzle,
                             CUtensorMapL2promotion, CUtensorMapFloatOOBfill);
}

extern "C" void kernel_launch(void* const* d_in, const int* in_sizes, int n_in, void* d_out, int out_size) {
    (void)in_sizes; (void)n_in; (void)out_size;
    static EncodeFn enc = nullptr;
    static Scratch* scratch = nullptr;
    if (!enc) {
        void* fn = nullptr;
        cudaDriverEntryPointQueryResult qr;
        cudaGetDriverEntryPoint("cuTensorMapEncodeTiled", &fn, cudaEnableDefault, &qr);
        enc = (EncodeFn)fn;
        cudaGetSymbolAddress((void**)&scratch, g_scratch);
        cudaFuncSetAttribute(wide_deep_kernel, cudaFuncAttributeMaxDynamicSharedMemorySize, SMEM_BYTES);
    }
    CUtensorMap tmW, tmT;
    {
        cuuint64_t gd[3] = {NH, ND, NF};
        cuuint64_t gs[2] = {NH * 2, (cuuint64_t)NH * 2 * ND};
        cuuint32_t bd[3] = {8, 16, 13};
        cuuint32_t es[3] = {1, 1, 1};
        enc(&tmW, CU_TENSOR_MAP_DATA_TYPE_BFLOAT16, 3, d_in[5], gd, gs, bd, es, CU_TENSOR_MAP_INTERLEAVE_NONE,
            CU_TENSOR_MAP_SWIZZLE_NONE, WPROMO, CU_TENSOR_MAP_FLOAT_OOB_FILL_NONE);
    }
    {
        cuuint64_t gd[2] = {ND, NV};
        cuuint64_t gs[1] = {ND * 2};
        cuuint32_t bd[2] = {64, 256};
        cuuint32_t es[2] = {1, 1};
        enc(&tmT, CU_TENSOR_MAP_DATA_TYPE_BFLOAT16, 2, d_in[1], gd, gs, bd, es, CU_TENSOR_MAP_INTERLEAVE_NONE,
            CU_TENSOR_MAP_SWIZZLE_128B, TPROMO, CU_TENSOR_MAP_FLOAT_OOB_FILL_NONE);
    }
    wide_deep_kernel<<<128, NTHREADS, SMEM_BYTES>>>(
        scratch, (const int*)d_in[0], 1.0f, tmW, tmT, (const __nv_bfloat16*)d_in[2], (const __nv_bfloat16*)d_in[3],
        (const __nv_bfloat16*)d_in[4], (const __nv_bfloat16*)d_in[6], (const __nv_bfloat16*)d_in[7],
        (const __nv_bfloat16*)d_in[8], (__nv_bfloat16*)d_out);
}
```

```cpp
#include <cuda_runtime.h>
#include <cuda_bf16.h>
#include <cuda.h>
#include <stdint.h>

namespace {

constexpr int NB = 4096, NF = 26, ND = 128, NV = 1000, NH = 512, NW = 13;
constexpr int NTHREADS = 384;
constexpr int SMEM_BYTES = 232448;
constexpr uint32_t SBASE = 1024;
constexpr uint32_t OFF_A = 8 * 128;
constexpr uint32_t OFF_IDX = OFF_A + 768 * 128;
constexpr uint32_t OFF_CVT = OFF_IDX + 3456;
constexpr uint32_t OFF_W = 824 * 128;
constexpr uint32_t OFF_MISC = 1032 * 128;
constexpr uint32_t OFF_B = 1056 * 128;
constexpr uint32_t OFF_Z = OFF_B - 128;
constexpr uint32_t BAR_W = OFF_MISC;
constexpr uint32_t BAR_T = OFF_MISC + 64;
constexpr uint32_t BAR_FREE = OFF_MISC + 112;
constexpr uint32_t BAR_DONE = OFF_MISC + 120;
constexpr uint32_t OFF_PAR = OFF_MISC + 128;
constexpr uint32_t OFF_RED = OFF_MISC + 256;
constexpr uint32_t OFF_WIDE = OFF_MISC + 2304;
constexpr uint32_t BAR_X = OFF_MISC + 2432;
constexpr uint32_t BAR_I = OFF_MISC + 2496;
constexpr uint32_t BAR_L = OFF_MISC + 2504;
constexpr uint32_t OFF_PERM = OFF_MISC + 2560;
constexpr int SPIN_LIMIT = 1 << 22;

struct alignas(1024) Scratch {
    uint4 part[64][2][64][32];
    uint4 logit[128][64][8];
    uint4 idx4[2][128][32];
    uint32_t idx1[2][128][32];
    uint32_t epoch, pad[3];
};
__device__ Scratch g_scratch;
#define STAMP(i) do {} while (0)
#define GSTAMP(i) do {} while (0)

__device__ __forceinline__ void mbar_init(uint32_t bar, int cnt) {
    asm volatile("mbarrier.init.shared::cta.b64 [%0], %1;" ::"r"(bar), "r"(cnt) : "memory");
}
__device__ __forceinline__ void mbar_expect(uint32_t bar, int bytes) {
    asm volatile("mbarrier.arrive.expect_tx.shared::cta.b64 _, [%0], %1;" ::"r"(bar), "r"(bytes) : "memory");
}
__device__ __forceinline__ void mbar_arrive(uint32_t bar) {
    asm volatile("mbarrier.arrive.shared::cta.b64 _, [%0];" ::"r"(bar) : "memory");
}
__device__ __forceinline__ void fault() { asm volatile("st.global.u32 [%0], %1;" ::"l"(0ull), "r"(0) : "memory"); }
__device__ __forceinline__ void mbar_wait(uint32_t bar) {
    asm volatile(
        "{\n"
        ".reg .pred p;\n"
        ".reg .u32 n;\n"
        "mov.u32 n, 0;\n"
        "LW_%=:\n"
        "mbarrier.try_wait.parity.shared::cta.b64 p, [%0], 0;\n"
        "@p bra LD_%=;\n"
        "add.u32 n, n, 1;\n"
        "setp.gt.u32 p, n, 1048576;\n"
        "@p st.global.u32 [%1], n;\n"
        "bra LW_%=;\n"
        "LD_%=:\n"
        "}\n" ::"r"(bar), "l"(0ull) : "memory");
}
__device__ __forceinline__ void tma2d(uint32_t dst, const CUtensorMap* tm, uint32_t bar, int c0, int c1) {
    asm volatile("cp.async.bulk.tensor.2d.shared::cluster.global.mbarrier::complete_tx::bytes [%0], [%1, {%3, %4}], [%2];"
                 ::"r"(dst), "l"(tm), "r"(bar), "r"(c0), "r"(c1) : "memory");
}
__device__ __forceinline__ void tma3d(uint32_t dst, const CUtensorMap* tm, uint32_t bar, int c0, int c1, int c2) {
    asm volatile("cp.async.bulk.tensor.3d.shared::cluster.global.mbarrier::complete_tx::bytes [%0], [%1, {%3, %4, %5}], [%2];"
                 ::"r"(dst), "l"(tm), "r"(bar), "r"(c0), "r"(c1), "r"(c2) : "memory");
}
__device__ __forceinline__ void bulk_g2s(uint32_t dst, const void* src, int bytes, uint32_t bar) {
    asm volatile("cp.async.bulk.shared::cluster.global.mbarrier::complete_tx::bytes [%0], [%1], %2, [%3];"
                 ::"r"(dst), "l"(src), "r"(bytes), "r"(bar) : "memory");
}
__device__ __forceinline__ uint32_t lds32(uint32_t addr) {
    uint32_t v;
    asm volatile("ld.shared.b32 %0, [%1];" : "=r"(v) : "r"(addr) : "memory");
    return v;
}
__device__ __forceinline__ uint32_t lds16(uint32_t addr) {
    uint32_t v;
    asm volatile("ld.shared.u16 %0, [%1];" : "=r"(v) : "r"(addr) : "memory");
    return v;
}
__device__ __forceinline__ uint64_t desc_a(uint32_t addr) {
    return (uint64_t)(addr >> 4) | ((uint64_t)1 << 16) | ((uint64_t)64 << 32) | ((uint64_t)1 << 62);
}
__device__ __forceinline__ uint64_t desc_w(uint32_t addr) {
    return (uint64_t)(addr >> 4) | ((uint64_t)8 << 16) | ((uint64_t)16 << 32);
}
#define R4(i) "+f"(d[i]), "+f"(d[i + 1]), "+f"(d[i + 2]), "+f"(d[i + 3])
template <int SCALE_D>
__device__ __forceinline__ void wgmma104(float (&d)[52], uint64_t da, uint64_t db) {
    asm volatile(
        "wgmma.mma_async.sync.aligned.m64n104k16.f32.bf16.bf16 "
        "{%0,%1,%2,%3,%4,%5,%6,%7,%8,%9,%10,%11,%12,%13,%14,%15,%16,%17,%18,%19,%20,%21,%22,%23,%24,%25,"
        "%26,%27,%28,%29,%30,%31,%32,%33,%34,%35,%36,%37,%38,%39,%40,%41,%42,%43,%44,%45,%46,%47,%48,%49,%50,%51}, "
        "%52, %53, %54, 1, 1, 0, 1;"
        : R4(0), R4(4), R4(8), R4(12), R4(16), R4(20), R4(24), R4(28), R4(32), R4(36), R4(40), R4(44), R4(48)
        : "l"(da), "l"(db), "n"(SCALE_D));
}
__device__ __forceinline__ void wg_fence() { asm volatile("wgmma.fence.sync.aligned;" ::: "memory"); }
__device__ __forceinline__ void wg_commit() { asm volatile("wgmma.commit_group.sync.aligned;" ::: "memory"); }
template <int N> __device__ __forceinline__ void wg_wait() { asm volatile("wgmma.wait_group.sync.aligned %0;" ::"n"(N) : "memory"); }

__device__ __forceinline__ uint32_t pack_bf16(float lo, float hi) {
    uint32_t r;
    asm("cvt.rn.bf16x2.f32 %0, %1, %2;" : "=r"(r) : "f"(hi), "f"(lo));
    return r;
}
__device__ __forceinline__ void cswap_alu(uint32_t& a, uint32_t& b, bool p) { const uint32_t x = a, y = b; a = p ? y : x; b = p ? x : y; }
__device__ __forceinline__ void cswap_fma(uint32_t& a, uint32_t& b, uint32_t p, float one) {
    asm("{\n.reg .pred q;\n.reg .f32 t;\nsetp.ne.u32 q, %2, 0;\nmul.f32 t, %0, %3;\n@q mul.f32 %0, %1, %3;\n@q mul.f32 %1, t, %3;\n}\n"
        : "+f"(*reinterpret_cast<float*>(&a)), "+f"(*reinterpret_cast<float*>(&b)) : "r"(p), "f"(one));
}
__device__ __forceinline__ void cswap4(uint32_t (&a)[4], uint32_t (&b)[4], uint32_t p, float one) {
    cswap_fma(a[0], b[0], p, one); cswap_alu(a[1], b[1], p); cswap_fma(a[2], b[2], p, one); cswap_fma(a[3], b[3], p, one);
}
__device__ __forceinline__ void sts128(uint32_t addr, const uint32_t (&r)[4]) {
    asm volatile("st.shared.v4.b32 [%0], {%1,%2,%3,%4};" ::"r"(addr), "r"(r[0]), "r"(r[1]), "r"(r[2]), "r"(r[3]) : "memory");
}
__device__ __forceinline__ void use_now(const uint32_t (&r)[4], float one) {
    asm volatile("{\n.reg .pred p;\nsetp.eq.f32 p, %4, 0f00000000;\n@p st.volatile.shared.v4.b32 [%5], {%0,%1,%2,%3};\n}\n"
                 ::"r"(r[0]), "r"(r[1]), "r"(r[2]), "r"(r[3]), "f"(one), "r"(OFF_MISC));
}
__device__ __forceinline__ void stm4(uint32_t addr, uint32_t a, uint32_t b, uint32_t c, uint32_t d) {
    asm volatile("stmatrix.sync.aligned.m8n8.x4.shared.b16 [%0], {%1,%2,%3,%4};" ::"r"(addr), "r"(a), "r"(b), "r"(c), "r"(d) : "memory");
}
__device__ __forceinline__ uint4 lds128(uint32_t addr) {
    uint4 v;
    asm volatile("ld.volatile.shared.v4.b32 {%0,%1,%2,%3}, [%4];" : "=r"(v.x), "=r"(v.y), "=r"(v.z), "=r"(v.w) : "r"(addr));
    return v;
}
__device__ __forceinline__ uint4 lds128_b(uint32_t rel) {
    uint4 v;
    asm volatile("ld.volatile.shared.v4.b32 {%0,%1,%2,%3}, [%4+135040];" : "=r"(v.x), "=r"(v.y), "=r"(v.z), "=r"(v.w) : "r"(rel));
    return v;
}
static_assert(OFF_Z == 135040, "immediate above");
__device__ __forceinline__ void mma_sel(float (&d)[4], const uint4& a, uint32_t b0, uint32_t b1) {
    asm volatile("mma.sync.aligned.m16n8k16.row.col.f32.bf16.bf16.f32 {%0,%1,%2,%3}, {%4,%5,%6,%7}, {%8,%9}, {%0,%1,%2,%3};"
                 : "+f"(d[0]), "+f"(d[1]), "+f"(d[2]), "+f"(d[3]) : "r"(a.x), "r"(a.y), "r"(a.z), "r"(a.w), "r"(b0), "r"(b1));
}
__device__ __forceinline__ uint4 ldg_rlx4(const void* p) {
    uint4 v;
    asm volatile("{\n.reg .b128 t;\nld.relaxed.gpu.global.b128 t, [%4];\nmov.b128 {%0,%1,%2,%3}, t;\n}\n"
                 : "=r"(v.x), "=r"(v.y), "=r"(v.z), "=r"(v.w) : "l"(p) : "memory");
    return v;
}
__device__ __forceinline__ uint4 ldg_rlx4v(const void* p) {
    uint4 v;
    asm volatile("ld.relaxed.gpu.global.v4.b32 {%0,%1,%2,%3}, [%4];" : "=r"(v.x), "=r"(v.y), "=r"(v.z), "=r"(v.w) : "l"(p) : "memory");
    return v;
}
__device__ __forceinline__ uint32_t ldg_rlx1(const void* p) {
    uint32_t v;
    asm volatile("ld.relaxed.gpu.global.b32 %0, [%1];" : "=r"(v) : "l"(p) : "memory");
    return v;
}
__device__ __forceinline__ void stg_rlx4(void* p, uint4 v) {
    asm volatile("{\n.reg .b128 t;\nmov.b128 t, {%1,%2,%3,%4};\nst.relaxed.gpu.global.b128 [%0], t;\n}\n"
                 ::"l"(p), "r"(v.x), "r"(v.y), "r"(v.z), "r"(v.w) : "memory");
}
__device__ __forceinline__ void stg_rlx1(void* p, uint32_t v) {
    asm volatile("st.relaxed.gpu.global.b32 [%0], %1;" ::"l"(p), "r"(v) : "memory");
}
__device__ __forceinline__ void pin_acc(float (&d)[52]) {
#pragma unroll
    for (int i = 0; i < 52; i++) asm volatile("" : "+f"(d[i])::"memory");
}
__device__ __forceinline__ float ldg_bf16(const void* p) {
    uint16_t v;
    asm volatile("ld.global.nc.u16 %0, [%1];" : "=h"(v) : "l"(p));
    return __uint_as_float((uint32_t)v << 16);
}

struct Codes { uint32_t w[5]; };
struct TrueT { static constexpr bool value = true; };
struct FalseT { static constexpr bool value = false; };
__host__ __device__ constexpr int posA(int i) { return 80 * (i >> 2) + 10 * (i & 1) + 33 * ((i >> 1) & 1); }
__host__ __device__ constexpr int posB(int i) { return i < 4 ? 80 * (i >> 1) + 20 + 33 * (i & 1) : 80 * (i - 4) + 66; }
__device__ __forceinline__ uint32_t window(const Codes& c, const int pos, const int tgt) {
    const int wd = pos / 32, b = pos % 32;
    if (b == tgt) return c.w[wd];
    if (b < tgt) return c.w[wd] << (tgt - b);
    if (b + (17 - tgt) <= 32) return c.w[wd] >> (b - tgt);
    return __funnelshift_r(c.w[wd], c.w[(wd + 1) % 5], b - tgt);
}
__device__ __forceinline__ void put(Codes& c, const int pos, const int bits, uint32_t v) {
    const int wd = pos / 32, b = pos % 32;
    c.w[wd] |= v << b;
    if (b + bits > 32) c.w[(wd + 1) % 5] |= v >> (32 - b);
}
__device__ __forceinline__ void load_codes(Codes& c, uint64_t p4, uint64_t p1) {
    const uint4 a = ldg_rlx4(reinterpret_cast<const void*>(p4));
    c.w[4] = ldg_rlx1(reinterpret_cast<const void*>(p1));
    c.w[0] = a.x; c.w[1] = a.y; c.w[2] = a.z; c.w[3] = a.w;
}

__global__ void __cluster_dims__(2, 1, 1) __launch_bounds__(NTHREADS, 1)
wide_deep_kernel(Scratch* __restrict__ sc, const int* __restrict__ idx, const float one,
                 const __grid_constant__ CUtensorMap tmW, const __grid_constant__ CUtensorMap tmT,
                 const __nv_bfloat16* __restrict__ x_wide,
                 const __nv_bfloat16* __restrict__ w_wide, const __nv_bfloat16* __restrict__ b_wide,
                 const __nv_bfloat16* __restrict__ b1, const __nv_bfloat16* __restrict__ W2,
                 const __nv_bfloat16* __restrict__ b2, __nv_bfloat16* __restrict__ out) {
    extern __shared__ __align__(1024) unsigned char smem[];
    const int tid = threadIdx.x, lane = tid & 31;
    const int bid = blockIdx.x;
    const int h = (bid >> 1) & 1;
    const int cg = ((bid >> 2) << 1) | (bid & 1);
    const int g = lane >> 2, q = lane & 3;
    const uint32_t cwin = (uint32_t)__cvta_generic_to_shared(smem) - SBASE;

    if (tid == 0) STAMP(15);
    GSTAMP(0);
    if (tid == 0) {
#pragma unroll
        for (int i = 0; i < 4; i++) mbar_init(cwin + BAR_W + 8 * i, 1);
        mbar_init(cwin + BAR_T, 1);
        mbar_init(cwin + BAR_I, 1);
        asm volatile("fence.mbarrier_init.release.cluster;" ::: "memory");
        mbar_expect(cwin + BAR_I, 32 * NF * 4 + 16);
        bulk_g2s(cwin + OFF_IDX, idx + bid * 32 * NF, 32 * NF * 4, cwin + BAR_I);
        bulk_g2s(cwin + OFF_IDX + 32 * NF * 4, &sc->epoch, 16, cwin + BAR_I);
#pragma unroll
        for (int ks = 0; ks < 4; ks++) {
            mbar_expect(cwin + BAR_W + 8 * ks, 3328);
            tma3d(cwin + OFF_W + ks * 3328, &tmW, cwin + BAR_W + 8 * ks, cg * 8, ks * 16, h * 13);
            if (ks == 0) {
                STAMP(14);
                mbar_expect(cwin + BAR_T, 32768);
                tma2d(cwin + OFF_A + 65536, &tmT, cwin + BAR_T, 0, 768);
            }
        }
    }
    const int warp = __shfl_sync(~0u, tid >> 5, 0);
    if (warp < 8) {
    if (warp == 0) asm volatile("bar.arrive 5, 160;" ::: "memory");
    asm volatile("bar.sync 1, 288;" ::: "memory");
    {
        if (warp < 4) {
            mbar_wait(cwin + BAR_I);
            if (tid < 104) {
                const uint32_t f = tid % 13;
                const uint32_t shl = f < 8 ? 0 : 3, sh2 = f < 12 ? 2 : 0;
#pragma unroll 2
                for (uint32_t e = tid; e < 32 * NF; e += 104) {
                    uint32_t v = lds32(cwin + OFF_IDX + e * 4);
                    v = ((int)v < 0) ? v + NV : v;
                    v = min(v, (uint32_t)(NV - 1));
                    const uint32_t hi = v >= 768;
                    const uint32_t a = f < 12 ? (hi ? 96 - 48 * 128 + ((v & 8) ? 2048 - 32 : 0) : 0) : (hi ? 96 - 16 * 128 : 64);
                    const uint32_t c = 8 + ((v & ~15u) << shl) + (f < 8 ? v & 15 : ((v & 15) << sh2) + a);
                    asm volatile("st.shared.u16 [%0], %1;" ::"r"(cwin + OFF_CVT + e * 2), "h"((uint16_t)c) : "memory");
                }
            }
            __syncwarp();
            asm volatile("bar.arrive 4, 256;" ::: "memory");
        } else {
            const int hh = warp & 1, s2 = (warp >> 1) & 1;
            mbar_wait(cwin + BAR_I);
            STAMP(14);
            const uint32_t tag = (lds32(cwin + OFF_IDX + 32 * NF * 4) & 1) ^ 1;
            {
                const uint32_t rowp = cwin + OFF_IDX + lane * NF * 4;
                uint32_t df[8], de = ~0u;
#pragma unroll
                for (int k = 0; k < 8; k++) {
                    const uint32_t b = lds32(rowp + (8 + (k & 3) + 13 * (k >> 2)) * 4) & 1;
                    df[k] = __ballot_sync(~0u, b) ^ (0u - b);
                }
#pragma unroll
                for (int k = 0; k < 2; k++) {
                    const uint32_t e = lds32(rowp + (12 + 13 * k) * 4);
                    de &= (__ballot_sync(~0u, e & 1) ^ (0u - (e & 1))) | (__ballot_sync(~0u, e & 2) ^ (0u - ((e >> 1) & 1)));
                }
                auto maj = [](uint32_t x, uint32_t y, uint32_t z) { return (x & y) | (z & (x | y)); };
                const uint32_t s1 = df[0] ^ df[1] ^ df[2], s2_ = df[3] ^ df[4] ^ df[5], s3 = df[6] ^ df[7] ^ s1;
                const uint32_t c1 = maj(df[0], df[1], df[2]), c2 = maj(df[3], df[4], df[5]), c3 = maj(df[6], df[7], s1), c4 = s2_ & s3;
                const uint32_t s5 = c1 ^ c2 ^ c3, d1 = maj(c1, c2, c3), d2 = s5 & c4;
                const uint32_t plane[5] = {de, d1 & d2, d1 ^ d2, s5 ^ c4, s2_ ^ s3};
                uint32_t un = ~0u, partner = 32;
#pragma unroll 1
                for (int round = 0; round < 2; round++) {
                    uint32_t m = un & ~(1u << lane);
#pragma unroll
                    for (int k = 0; k < 5; k++) { const uint32_t t = m & plane[k]; m = t ? t : m; }
                    const uint32_t j = (__ffs(__funnelshift_l(m, m, lane)) - 1 - lane) & 31;
                    const bool hit = __shfl_sync(~0u, j, j) == (uint32_t)lane && partner == 32 && m != 0;
                    if (hit) partner = j;
                    un &= ~__ballot_sync(~0u, hit);
                }
                const uint32_t lt = (1u << lane) - 1, lead = __ballot_sync(~0u, partner != 32 && (uint32_t)lane < partner);
                const uint32_t slot = partner != 32 ? 2 * __popc(lead & ((1u << min((uint32_t)lane, partner)) - 1)) + ((uint32_t)lane > partner)
                                                    : 2 * __popc(lead) + __popc(un & lt);
                asm volatile("st.shared.b32 [%0], %1;" ::"r"(cwin + OFF_PERM + (((slot & 7) << 2) | (slot >> 3)) * 4), "r"(lane) : "memory");
                __syncwarp();
            }
            uint32_t rp[2];
#pragma unroll
            for (int gm = 0; gm < 2; gm++) rp[gm] = cwin + OFF_CVT + (lds32(cwin + OFF_PERM + (4 * g + 2 * gm + s2) * 4) * NF + hh * 13) * 2;
            asm volatile("bar.sync 4, 256;" ::: "memory");
            uint32_t av[4], fv[2], evr[2];
#pragma unroll
            for (int gm = 0; gm < 2; gm++) {
                av[2 * gm] = lds16(rp[gm] + (4 * (g & 1) + q) * 2);
                av[2 * gm + 1] = lds16(rp[gm] + (4 * ((g & 1) ^ 1) + q) * 2);
                fv[gm] = lds16(rp[gm] + (8 + q) * 2);
                evr[gm] = lds16(rp[gm] + 12 * 2);
            }
            auto ecode_of = [](uint32_t c0, uint32_t half) { const uint32_t cp = (c0 ^ (half << 2)) & 4; return (c0 + 4 * cp) ^ cp; };
            const uint32_t isY = g & 1, qsh = lane & 24;
            uint32_t bc[3], mine[2], mv = 0, cls = 0, inS = 0;
#pragma unroll
            for (int gm = 0; gm < 2; gm++) {
                const uint32_t v = fv[gm];
                const uint32_t par = __ballot_sync(~0u, v & 4) >> qsh;
                const uint32_t eq = ~(par ^ (par >> 4)) & 15;
                const uint32_t eo = __shfl_xor_sync(~0u, evr[gm], 4);
                const uint32_t eX = (isY ? eo : evr[gm]) & 3, eY = (isY ? evr[gm] : eo) & 3;
                uint32_t mX = (eq >> eX) & 1, mY = (eq >> eY) & 1;
                if (eX == eY) mY = 0;
                const int m = __popc(eq);
                const bool res = m <= (int)(2 + mX + mY);
                if (!res) { mX = 0; mY = 0; }
                const int kX = max(m - 1 - (int)mY, (int)mX);
                const uint32_t eqr = res ? eq : 0;
                uint32_t lowk = 0, t = eqr;
                if (kX > 0) { lowk = t & (0u - t); t ^= lowk; }
                if (kX > 1) lowk |= t & (0u - t);
                mine[gm] = isY ? eqr ^ lowk : lowk;
                mv |= eqr & ~par;
                cls |= (eX | (eY << 2)) << (4 * gm);
                inS |= ((mX ^ 1) | ((mY ^ 1) << 1)) << (2 * gm);
                const uint32_t emain = isY ? mY : mX;
                const uint32_t zc = (__ffs(eqr & ~(mX << eX) & ~(mY << eY)) - 1) & 3;
                const bool moved = (mine[gm] >> q) & 1, first = (mine[gm] & ((1u << q) - 1)) == 0;
                const uint32_t ce = ecode_of(evr[gm], ~(par >> (evr[gm] & 3))), cz = zc + ((~(par >> zc) & 1) << 2);
                bc[gm] = !moved ? v + q : (first && emain) ? ce : cz;
            }
            {
                const uint32_t up = q >> 1, t = q & 1;
                const uint32_t my_ev = up ? evr[1] : evr[0];
                const uint32_t me = 2 * up + isY, myE = (inS >> me) & 1, e = my_ev & 3;
                uint32_t half = mv >> e;
#pragma unroll
                for (int k = 0; k < 3; k++) half += (k < me && ((inS >> k) & 1) && ((cls >> (2 * k)) & 3) == e) ? 1 : 0;
                uint32_t fm = up ? mine[1] : mine[0];
                if (!myE && t) fm &= fm - 1;
                const bool useE = myE && !t, act = useE || fm != 0;
                const uint32_t fc = (__ffs(fm) - 1) & 3;
                const uint32_t fvv = lds16((up ? rp[1] : rp[0]) + (8 + fc) * 2);
                const uint32_t code = useE ? ecode_of(my_ev, half) : fvv + fc;
                uint32_t used = act ? 1u << (code & 7) : 0;
                used |= __shfl_xor_sync(~0u, used, 1);
                used |= __shfl_xor_sync(~0u, used, 2);
                used |= __shfl_xor_sync(~0u, used, 4);
                bc[2] = act ? code : (__ffs(~used) - 1) & 7;
            }
            Codes c;
            c.w[0] = 0; c.w[1] = 0; c.w[2] = tag << 15; c.w[3] = 0; c.w[4] = 0;
#pragma unroll
            for (int k = 0; k < 4; k++) put(c, posA(k), 10, av[k]);
            put(c, posB(0), 13, bc[0]);
            put(c, posB(1), 13, bc[1]);
            put(c, posB(4), 13, bc[2]);
            const uint32_t xch = cwin + OFF_RED + hh * 512 + lane * 16;
            if (s2) asm volatile("st.shared.v4.b32 [%0], {%1,%2,%3,%3};" ::"r"(xch), "r"(c.w[0]), "r"(c.w[1]), "r"(c.w[2]) : "memory");
            asm volatile("bar.sync %0, 64;" ::"r"(7 + hh) : "memory");
            if (!s2) {
                const uint4 o = lds128(xch);
                stg_rlx4(&sc->idx4[hh][bid][lane], make_uint4(c.w[0], c.w[1], c.w[2] | (o.x << 16), __funnelshift_r(o.x, o.y, 16)));
                stg_rlx1(&sc->idx1[hh][bid][lane], __funnelshift_r(o.y, o.z, 16));
            }
        }
    }
    asm volatile("setmaxnreg.inc.sync.aligned.u32 240;");
    STAMP(0);

    const int wg = warp >> 2;
    uint32_t pkA[2][2][2][4], pkF[2][2][4], pkE[2][2];
    Codes cd[2][2];
    uint64_t pc4, pc2;
    const uint32_t slab = cwin + (uint32_t)(wg * 8 + (warp & 3)) * 2048;
    const uint32_t stA = OFF_A + slab + (uint32_t)g * 128 + (uint32_t)((g & 1) * 4 + q) * 16;
    {
        float acc[2][52];
        const uint64_t dw = desc_w(OFF_W);
        const uint64_t da0 = desc_a(OFF_A + 128 * wg * 128), da1 = desc_a(OFF_B + 128 * wg * 128);
        auto pack_entry = [](uint32_t (&e)[4], const float (&a)[52], const int i, const int rs) {
#pragma unroll
            for (int x = 0; x < 4; x++) e[x] = pack_bf16(a[16 * i + 4 * x + 2 * rs], a[16 * i + 4 * x + 2 * rs + 1]);
        };
        {
            float accp[2][52];
            mbar_wait(cwin + BAR_T);
#pragma unroll
            for (int ks = 0; ks < 4; ks++) {
                mbar_wait(cwin + BAR_W + 8 * ks);
                mbar_wait(cwin + BAR_X + 8 * ks);
                if (ks == 0) { STAMP(1); GSTAMP(1); }
                wg_fence();
                if (ks == 0) { wgmma104<0>(accp[0], da0 + 4096, dw); wgmma104<0>(accp[1], da0 + 4096 + 512, dw); }
                else { wgmma104<1>(accp[0], da0 + 4096 + ks * 2, dw + ks * 208); wgmma104<1>(accp[1], da0 + 4096 + 512 + ks * 2, dw + ks * 208); }
            }
            mbar_wait(cwin + BAR_T + 32);
            wg_fence();
            wgmma104<0>(acc[0], da0, dw);
            wgmma104<0>(acc[1], da0 + 512, dw);
#pragma unroll
            for (int ks = 1; ks < 4; ks++) { wgmma104<1>(acc[0], da0 + ks * 2, dw + ks * 208); wgmma104<1>(acc[1], da0 + 512 + ks * 2, dw + ks * 208); }
            mbar_wait(cwin + BAR_T + 8);
#pragma unroll
            for (int ks = 4; ks < 8; ks++) {
                mbar_wait(cwin + BAR_W + 8 * ks);
                mbar_wait(cwin + BAR_X + 8 * ks);
                wg_fence();
                wgmma104<1>(accp[0], da1 + 4096 + (ks & 3) * 2, dw + ks * 208);
                wgmma104<1>(accp[1], da1 + 4096 + 512 + (ks & 3) * 2, dw + ks * 208);
            }
            wg_commit();
            mbar_wait(cwin + BAR_T + 40);
            wg_fence();
            wgmma104<1>(acc[0], da1, dw + 4 * 208);
            wgmma104<1>(acc[0], da1 + 2, dw + 5 * 208);
            wg_commit();
            wg_wait<1>();
            pin_acc(accp[0]);
            pin_acc(accp[1]);
            if (lane == 0) mbar_arrive(cwin + BAR_FREE);
            auto park = [&](const int u, const int rs) {
                pack_entry(pkA[u][rs][0], accp[u], 0, rs);
                pack_entry(pkA[u][rs][1], accp[u], 1, rs);
                cswap4(pkA[u][rs][0], pkA[u][rs][1], g & 1, one);
                pack_entry(pkF[u][rs], accp[u], 2, rs);
                pkE[u][rs] = pack_bf16(accp[u][48 + 2 * rs], accp[u][49 + 2 * rs]);
                use_now(pkA[u][rs][0], one);
                use_now(pkA[u][rs][1], one);
                use_now(pkF[u][rs], one);
            };
            wgmma104<1>(acc[0], da1 + 4, dw + 6 * 208);
            wgmma104<1>(acc[0], da1 + 6, dw + 7 * 208);
            wg_commit();
#pragma unroll
            for (int ks = 4; ks < 8; ks++) {
                park((ks >> 1) & 1, ks & 1);
                wgmma104<1>(acc[1], da1 + 512 + (ks & 3) * 2, dw + ks * 208);
            }
            wg_commit();
            STAMP(2);
            GSTAMP(2);
        }
        {
            const uint32_t t[4] = {pkE[0][0], pkE[0][1], pkE[1][0], pkE[1][1]};
            use_now(t, one);
        }
        const uint32_t stF = OFF_B + slab + (uint32_t)lane * 16;
        const uint32_t stE = OFF_B + slab + 1024 + (((uint32_t)lane * 16) ^ ((uint32_t)(lane >> 4) * 64));
        pc4 = reinterpret_cast<uint64_t>(&sc->idx4[h][(1 - h) * 64 + 2 * warp][lane]);
        pc2 = reinterpret_cast<uint64_t>(&sc->idx1[h][(1 - h) * 64 + 2 * warp][lane]);
        auto tile = [&](auto MMA, const int s, const int u) {
            constexpr bool mma = decltype(MMA)::value;
            uint32_t ea[2][2][4], ef[2][4], ee[2];
#pragma unroll
            for (int rs = 0; rs < 2; rs++) {
                pack_entry(ea[rs][0], acc[u], 0, rs);
                pack_entry(ea[rs][1], acc[u], 1, rs);
                pack_entry(ef[rs], acc[u], 2, rs);
                ee[rs] = pack_bf16(acc[u][48 + 2 * rs], acc[u][49 + 2 * rs]);
            }
            const uint64_t off = (uint64_t)(2048 * (s + 1) + 512 * u);
            auto H = [&](const int ks) { if (mma) wgmma104<1>(acc[u], (ks < 4 ? da0 : da1) + off + (ks & 3) * 2, dw + ks * 208); };
            if (mma) {
                if (u == 0) mbar_wait(cwin + BAR_T + 16 + 8 * s);
                wg_fence();
                wgmma104<0>(acc[u], da0 + off, dw);
            }
            asm volatile("bar.sync %0, 128;" ::"r"(2 + wg) : "memory");
            const uint32_t so = s * 32768 + u * 8192;
            sts128(stF + so, ef[0]);
            H(1);
            sts128(stF + so + 512, ef[1]);
            H(2);
            stm4(stE + so, ee[0], ee[1], ee[0], ee[1]);
            H(3);
            if (mma) {
                sts128(stF + so + 1536, pkF[u][0]);
#pragma unroll
                for (int x = 0; x < 4; x++) pkF[u][0][x] = pkF[u][1][x];
            } else {
                stm4(stE + so + 512, pkE[u][0], pkE[u][1], pkE[u][0], pkE[u][1]);
            }
            H(4);
            cswap4(ea[0][0], ea[0][1], g & 1, one);
            sts128(stA + so, ea[0][0]);
            H(5);
            sts128((stA + so) ^ 64, ea[0][1]);
            H(6);
            cswap4(ea[1][0], ea[1][1], g & 1, one);
            sts128(stA + so + 1024, ea[1][0]);
            H(7);
            if (mma) wg_commit();
            sts128((stA + so + 1024) ^ 64, ea[1][1]);
        };
#pragma unroll
        for (int s = 0; s < 2; s++) {
#pragma unroll
            for (int u = 0; u < 2; u++) {
                wg_wait<1>();
                pin_acc(acc[u]);
                if (u == 0) STAMP(3 + 2 * s);
                tile(TrueT{}, s, u);
                if (s == 1) {
                    load_codes(cd[u][0], pc4 + u * 16 * 512, pc2 + u * 16 * 128);
                    load_codes(cd[u][1], pc4 + u * 16 * 512 + 512, pc2 + u * 16 * 128 + 128);
                }
                if (u == 1) STAMP(4 + 2 * s);
            }
        }
        wg_wait<1>();
        pin_acc(acc[0]);
        STAMP(7);
        tile(FalseT{}, 2, 0);
        wg_wait<0>();
        pin_acc(acc[1]);
        if (lane == 0) mbar_arrive(cwin + BAR_DONE);
        tile(FalseT{}, 2, 1);
        STAMP(8);
    }
    mbar_wait(cwin + BAR_DONE);
#pragma unroll
    for (int u = 0; u < 2; u++)
#pragma unroll
        for (int rs = 0; rs < 2; rs++) {
            sts128(stA + 3 * 32768 + u * 8192 + rs * 1024, pkA[u][rs][0]);
            sts128((stA + 3 * 32768 + u * 8192 + rs * 1024) ^ 64, pkA[u][rs][1]);
        }
    uint32_t epoch;
    float bias[4], w2[4];
    asm volatile("ld.shared.b32 %0, [%1];" : "=r"(epoch) : "r"(cwin + OFF_PAR + 64) : "memory");
    asm volatile("ld.shared.v4.f32 {%0,%1,%2,%3}, [%4];" : "=f"(bias[0]), "=f"(bias[1]), "=f"(bias[2]), "=f"(bias[3]) : "r"(cwin + OFF_PAR + (q & 1) * 16) : "memory");
    asm volatile("ld.shared.v4.f32 {%0,%1,%2,%3}, [%4];" : "=f"(w2[0]), "=f"(w2[1]), "=f"(w2[2]), "=f"(w2[3]) : "r"(cwin + OFF_PAR + 32 + (q & 1) * 16) : "memory");
    uint32_t tag = (epoch & 1) ^ 1;
    const uint32_t tagm = 0u - tag;
    uint32_t offA0 = cwin | ((uint32_t)(4 * (g & 1) + q) << 4), offA1 = cwin | ((uint32_t)(4 * ((g + 1) & 1) + q) << 4), offB = cwin;
    uint32_t sel[3][2];
#pragma unroll
    for (int u = 0; u < 2; u++) {
        sel[u][0] = g == 4 * u ? 0x3F80u : (g == 4 * u + 1 ? 0x3F800000u : 0u);
        sel[u][1] = g == 4 * u + 2 ? 0x3F80u : (g == 4 * u + 3 ? 0x3F800000u : 0u);
    }
    sel[2][0] = q < 2 ? sel[0][0] : sel[1][0];
    sel[2][1] = q < 2 ? sel[0][1] : sel[1][1];
    uint64_t ppart = reinterpret_cast<uint64_t>(&sc->part[cg][1 - h][2 * warp][lane]);
    uint64_t plog = reinterpret_cast<uint64_t>(reinterpret_cast<uint32_t*>(&sc->logit[h * 64 + 2 * warp][cg][0]) + lane);
    const int dhalf = 2 * h - 1;
    auto validate = [&](Codes (&c)[2], const uint64_t p4, const uint64_t p2) {
        auto stale = [&]() { return ((((c[0].w[2] ^ tagm) | (c[1].w[2] ^ tagm)) & 0x8000u) | (((c[0].w[4] ^ tagm) | (c[1].w[4] ^ tagm)) & 0x80000000u)) != 0; };
        if (__any_sync(~0u, stale())) {
            int spins = 0;
            do {
                load_codes(c[0], p4, p2);
                load_codes(c[1], p4 + 512, p2 + 128);
                if (++spins > SPIN_LIMIT) fault();
            } while (__any_sync(~0u, stale()));
        }
    };
    uint4 va[2][8], pin[2];
    auto load_a = [&](const Codes (&c)[2]) {
#pragma unroll
        for (int k = 0; k < 8; k++)
#pragma unroll
            for (int u = 0; u < 2; u++) {
                const int kk = (k >> 1) + (k & 1) * 4;
                va[u][kk] = lds128((window(c[u], posA(kk), 7) & 0x1FF80u) | ((kk & 1) ? offA1 : offA0));
            }
    };
    validate(cd[0], pc4, pc2);
    asm volatile("bar.sync 1, 256;" ::: "memory");
    STAMP(9);
    GSTAMP(3);
    load_a(cd[0]);
#pragma unroll 1
    for (int own = 0; own < 2; own++) {
#pragma unroll
        for (int i = 0; i < 4; i++) {
            Codes(&c)[2] = cd[i & 1];
            const bool more = i < 3 || !own;
            const uint64_t n4 = i < 3 ? pc4 + (i + 1) * 16 * 512 : pc4 + dhalf * 64 * 512;
            const uint64_t n2 = i < 3 ? pc2 + (i + 1) * 16 * 128 : pc2 + dhalf * 64 * 128;
            uint4 vb[2][6];
#pragma unroll
            for (int k = 0; k < 3; k++)
#pragma unroll
                for (int u = 0; u < 2; u++) {
                    const int k0 = k < 2 ? k : 4, k1 = k < 2 ? k + 2 : 5;
                    vb[u][k0] = lds128_b((window(c[u], posB(k0), 4) & 0x1FFF0u) | offB);
                    vb[u][k1] = lds128_b((window(c[u], posB(k1), 4) & 0x1FFF0u) | offB);
                }
            if (more) validate(cd[(i + 1) & 1], n4, n2);
            float d[4][4];
            if (own) {
                pin[0].x ^= tag; pin[1].x ^= tag;
                if (__any_sync(~0u, ((pin[0].x | pin[1].x) & 1u) != 0)) {
                    int spins = 0;
                    do {
#pragma unroll
                        for (int u = 0; u < 2; u++) { pin[u] = ldg_rlx4(reinterpret_cast<const void*>(ppart + (i * 16 + u) * 512)); pin[u].x ^= tag; }
                        if (++spins > SPIN_LIMIT) fault();
                    } while (__any_sync(~0u, ((pin[0].x | pin[1].x) & 1u) != 0));
                }
#pragma unroll
                for (int s = 0; s < 4; s++) {
                    const uint32_t p0 = (s & 1) ? pin[s >> 1].z : pin[s >> 1].x, p1 = (s & 1) ? pin[s >> 1].w : pin[s >> 1].y;
                    d[s][0] = bias[0] + __uint_as_float(p0 << 16); d[s][1] = bias[1] + __uint_as_float(p0 & 0xFFFF0000u);
                    d[s][2] = bias[2] + __uint_as_float(p1 << 16); d[s][3] = bias[3] + __uint_as_float(p1 & 0xFFFF0000u);
                }
            } else {
#pragma unroll
                for (int s = 0; s < 4; s++)
#pragma unroll
                    for (int k = 0; k < 4; k++) d[s][k] = 0.f;
            }
            if (i < 3 ? own : !own) {
                const uint64_t np = i < 3 ? ppart + (i + 1) * 16 * 512 : ppart + dhalf * 32768;
#pragma unroll
                for (int u = 0; u < 2; u++) pin[u] = ldg_rlx4(reinterpret_cast<const void*>(np + u * 512));
            }
#pragma unroll
            for (int k = 0; k < 4; k++)
#pragma unroll
                for (int u = 0; u < 2; u++) {
                    mma_sel(d[2 * u], va[u][k], sel[k >> 1][0], sel[k >> 1][1]);
                    mma_sel(d[2 * u + 1], va[u][k + 4], sel[k >> 1][0], sel[k >> 1][1]);
                }
            if (more) load_a(cd[(i + 1) & 1]);
            if (i < 2) {
                load_codes(c[0], pc4 + (i + 2) * 16 * 512, pc2 + (i + 2) * 16 * 128);
                load_codes(c[1], pc4 + (i + 2) * 16 * 512 + 512, pc2 + (i + 2) * 16 * 128 + 128);
            } else if (!own) {
                load_codes(c[0], pc4 + dhalf * 64 * 512 + (i - 2) * 16 * 512, pc2 + dhalf * 64 * 128 + (i - 2) * 16 * 128);
                load_codes(c[1], pc4 + dhalf * 64 * 512 + (i - 2) * 16 * 512 + 512, pc2 + dhalf * 64 * 128 + (i - 2) * 16 * 128 + 128);
            }
#pragma unroll
            for (int k = 0; k < 3; k++) {
#pragma unroll
                for (int u = 0; u < 2; u++) {
                    mma_sel(d[2 * u], vb[u][k < 2 ? k : 4], sel[k][0], sel[k][1]);
                    mma_sel(d[2 * u + 1], vb[u][k < 2 ? k + 2 : 5], sel[k][0], sel[k][1]);
                }
            }
            if (!own) {
#pragma unroll
                for (int u = 0; u < 2; u++) {
                    const uint32_t x0 = ((__float_as_uint(d[2 * u][0]) + 0x10000u) & 0xFFFE0000u) | (tag << 16);
                    stg_rlx4(reinterpret_cast<void*>(ppart + (i * 16 + u) * 512),
                             make_uint4(pack_bf16(__uint_as_float(x0), d[2 * u][1]), pack_bf16(d[2 * u][2], d[2 * u][3]),
                                        pack_bf16(d[2 * u + 1][0], d[2 * u + 1][1]), pack_bf16(d[2 * u + 1][2], d[2 * u + 1][3])));
                }
            } else {
                float t[4];
#pragma unroll
                for (int s = 0; s < 4; s++)
                    t[s] = fmaf(fmaxf(d[s][1], 0.f), w2[1], fmaxf(d[s][0], 0.f) * w2[0]) + fmaf(fmaxf(d[s][3], 0.f), w2[3], fmaxf(d[s][2], 0.f) * w2[2]);
#pragma unroll
                for (int u = 0; u < 2; u++) {
                    const float keep = (q & 1) ? t[2 * u + 1] : t[2 * u], send = (q & 1) ? t[2 * u] : t[2 * u + 1];
                    const float res = keep + __shfl_xor_sync(~0u, send, 1);
                    stg_rlx1(reinterpret_cast<void*>(plog + (i * 16 + u) * 8192), (__float_as_uint(res) & ~1u) | tag);
                }
            }
        }
        if (!own) { STAMP(13); GSTAMP(4); }
        if (!own) mbar_wait(cwin + BAR_L);
        ppart += (int64_t)dhalf * 32768;
        pc4 += (int64_t)dhalf * 64 * 512;
        pc2 += (int64_t)dhalf * 64 * 128;
    }
    STAMP(10);
    GSTAMP(5);

    {
        const uint4* lp = &sc->logit[bid][0][0] + tid;
        const uint32_t orow = lds32(cwin + OFF_PERM + lane * 4);
        uint4 v, y;
        int spins = 0;
        while (true) {
            v = ldg_rlx4v(lp);
            y = ldg_rlx4v(lp + 256);
            uint32_t bad;
            asm("{\n.reg .b32 a, b, c;\nlop3.b32 a, %1, %2, %9, 0x7e;\nlop3.b32 b, %3, %4, %9, 0x7e;\nlop3.b32 c, %5, %6, %9, 0x7e;\n"
                "lop3.b32 a, a, b, c, 0xfe;\nlop3.b32 b, %7, %8, %9, 0x7e;\nlop3.b32 %0, a, b, 1, 0xa8;\n}\n"
                : "=r"(bad) : "r"(v.x), "r"(v.y), "r"(v.z), "r"(v.w), "r"(y.x), "r"(y.y), "r"(y.z), "r"(y.w), "r"(tag));
            if (!__any_sync(~0u, bad)) break;
            if (++spins > SPIN_LIMIT) fault();
        }
        STAMP(11);
        float s0 = __uint_as_float(v.x ^ tag) + __uint_as_float(y.x ^ tag), s1 = __uint_as_float(v.y ^ tag) + __uint_as_float(y.y ^ tag);
        float s2 = __uint_as_float(v.z ^ tag) + __uint_as_float(y.z ^ tag), s3 = __uint_as_float(v.w ^ tag) + __uint_as_float(y.w ^ tag);
#pragma unroll
        for (int o = 8; o < 32; o <<= 1) {
            s0 += __shfl_xor_sync(~0u, s0, o); s1 += __shfl_xor_sync(~0u, s1, o);
            s2 += __shfl_xor_sync(~0u, s2, o); s3 += __shfl_xor_sync(~0u, s3, o);
        }
        if (lane < 8)
            asm volatile("st.shared.v4.f32 [%0], {%1,%2,%3,%4};" ::"r"(cwin + OFF_RED + warp * 128 + lane * 16), "f"(s0), "f"(s1), "f"(s2), "f"(s3) : "memory");
        asm volatile("bar.sync 6, 288;" ::: "memory");
        if (warp == 0) {
            float x[9];
#pragma unroll
            for (int i = 0; i < 9; i++) x[i] = __uint_as_float(lds32(cwin + (i < 8 ? OFF_RED + i * 128 + lane * 4 : OFF_WIDE + orow * 4)));
            const float z = (((x[0] + x[1]) + (x[2] + x[3])) + ((x[4] + x[5]) + (x[6] + x[7]))) + x[8];
            out[bid * 32 + orow] = __float2bfloat16(__fdividef(1.f, 1.f + __expf(-z)));
            if (bid == 0 && lane == 0) stg_rlx1(&sc->epoch, epoch + 1);
        }
        STAMP(12);
    }
    } else {
        asm volatile("setmaxnreg.dec.sync.aligned.u32 24;");
        if (warp != 8) {
            if (lane == 0) {
                if (warp == 9) {
#pragma unroll
                    for (int i = 4; i < 8; i++) mbar_init(cwin + BAR_W + 8 * i, 1);
                    mbar_init(cwin + BAR_FREE, 8);
                    mbar_init(cwin + BAR_DONE, 9);
                    mbar_init(cwin + BAR_L, 3);
                } else if (warp == 10) {
#pragma unroll
                    for (int i = 1; i < 6; i++) mbar_init(cwin + BAR_T + 8 * i, 1);
                } else {
#pragma unroll
                    for (int i = 0; i < 8; i++) mbar_init(cwin + BAR_X + 8 * i, 3);
                }
                asm volatile("fence.mbarrier_init.release.cluster;" ::: "memory");
            }
            __syncwarp();
            asm volatile("bar.sync 5, 160;" ::: "memory");
            const uint32_t xh = (lane >> 3) & 1;
            uint32_t x0 = cwin + OFF_W + (warp - 9) * 1024 + ((lane & 7) + (lane >> 4) * 8) * 16;
#pragma unroll 1
            for (int ks = 0; ks < 8; ks++, x0 += 3328) {
                mbar_wait(cwin + BAR_W + 8 * ks);
                STAMP(ks);
                uint32_t lo[4], hi[4];
#pragma unroll
                for (int x = 0; x < 4; x++)
                    asm volatile("ld.shared.v2.b32 {%0,%1}, [%2];" : "=r"(lo[x]), "=r"(hi[x]) : "r"(x0 + x * 256 + xh * 8) : "memory");
                __syncwarp();
                sts128(x0 + xh * 512, lo);
                sts128(x0 + xh * 512 + 256, hi);
                asm volatile("fence.proxy.async.shared::cta;" ::: "memory");
                __syncwarp();
                if (lane == 0) mbar_arrive(cwin + BAR_X + 8 * ks);
                STAMP(8 + ks);
            }
            mbar_wait(cwin + BAR_DONE);
            const uint32_t stale = lds32(cwin + OFF_PAR + 64) & 1;
#pragma unroll 1
            for (int i = tid - 288; i < 512; i += 96) stg_rlx4(&sc->logit[h * 64 + (i >> 3)][cg][i & 7], make_uint4(stale, stale, stale, stale));
            __syncwarp();
            if (lane == 0) mbar_arrive(cwin + BAR_L);
            if (warp == 10) {
                const __nv_bfloat16* xp = x_wide + (bid * 32 + lane) * NW;
                const float wv = ldg_bf16(lane < NW ? w_wide + lane : (lane == NW ? b_wide : b2));
                float wide = __shfl_sync(~0u, wv, NW) + __shfl_sync(~0u, wv, NW + 1);
#pragma unroll 1
                for (int i = 0; i < NW; i++) wide = fmaf(ldg_bf16(xp + i), __shfl_sync(~0u, wv, i), wide);
                asm volatile("st.shared.f32 [%0], %1;" ::"r"(cwin + OFF_WIDE + lane * 4), "f"(wide) : "memory");
                asm volatile("bar.arrive 6, 288;" ::: "memory");
            }
        } else {
            asm volatile("bar.sync 5, 160;" ::: "memory");
            asm volatile("bar.arrive 1, 288;" ::: "memory");
            if (lane == 0) {
#pragma unroll 1
                for (int ks = 3; ks < 8; ks++) {
                    if (ks > 3) {
                        mbar_expect(cwin + BAR_W + 8 * ks, 3328);
                        tma3d(cwin + OFF_W + ks * 3328, &tmW, cwin + BAR_W + 8 * ks, cg * 8, ks * 16, h * 13);
                    }
                    STAMP(ks);
                    if ((0xA8 >> ks) & 1) {
                        const int hf = ks >> 2, first = ks == 5;
                        const uint32_t bar = cwin + BAR_T + 8 * hf + (first ? 0 : 32);
                        mbar_expect(bar, 32768);
                        tma2d(cwin + (hf ? OFF_B : OFF_A) + (first ? 65536 : 0), &tmT, bar, 64 * hf, first ? 768 : 0);
                        STAMP(8 + ks);
                    }
                }
                if ((cwin & 0xFFFFFFu) != 0) fault();
                mbar_expect(cwin + BAR_T + 16, 65536);
                tma2d(cwin + OFF_A + 32768, &tmT, cwin + BAR_T + 16, 0, 256);
                tma2d(cwin + OFF_B + 32768, &tmT, cwin + BAR_T + 16, 64, 256);
            }
            __syncwarp();
            {
                const uint32_t* pp = lane < 4 ? reinterpret_cast<const uint32_t*>(b1) + cg * 4 + lane
                                   : lane < 8 ? reinterpret_cast<const uint32_t*>(W2) + cg * 4 + lane - 4 : &sc->epoch;
                const uint32_t e = ldg_rlx1(pp);
                asm volatile("st.shared.b32 [%0], %1;" ::"r"(cwin + OFF_Z + lane * 4), "r"(0) : "memory");
                if (lane <= 8)
                    asm volatile("st.shared.v2.b32 [%0], {%1,%2};" ::"r"(cwin + OFF_PAR + lane * 8), "r"(lane < 8 ? e << 16 : e), "r"(e & 0xffff0000u) : "memory");
                __syncwarp();
            }
            if (lane == 0) {
                mbar_arrive(cwin + BAR_DONE);
                mbar_wait(cwin + BAR_FREE);
                mbar_expect(cwin + BAR_T + 24, 65536);
                tma2d(cwin + OFF_A + 65536, &tmT, cwin + BAR_T + 24, 0, 512);
                tma2d(cwin + OFF_B + 65536, &tmT, cwin + BAR_T + 24, 64, 512);
            }
        }
    }
}

__global__ void __launch_bounds__(NH) wide_deep_fallback(const int* __restrict__ idx, const __nv_bfloat16* __restrict__ table,
                                                         const __nv_bfloat16* __restrict__ x_wide, const __nv_bfloat16* __restrict__ w_wide,
                                                         const __nv_bfloat16* __restrict__ b_wide, const __nv_bfloat16* __restrict__ W1,
                                                         const __nv_bfloat16* __restrict__ b1, const __nv_bfloat16* __restrict__ W2,
                                                         const __nv_bfloat16* __restrict__ b2, __nv_bfloat16* __restrict__ out) {
    __shared__ float emb[NF * ND];
    __shared__ float red[NH / 32];
    const int b = blockIdx.x, c = threadIdx.x;
    for (int i = c; i < NF * ND; i += NH) {
        int v = idx[b * NF + i / ND];
        v = v < 0 ? v + NV : v;
        emb[i] = __bfloat162float(table[min(v, NV - 1) * ND + i % ND]);
    }
    __syncthreads();
    float hsum = __bfloat162float(b1[c]);
    for (int k = 0; k < NF * ND; k++) hsum = fmaf(emb[k], __bfloat162float(W1[(size_t)k * NH + c]), hsum);
    float t = fmaxf(hsum, 0.f) * __bfloat162float(W2[c]);
    for (int o = 16; o; o >>= 1) t += __shfl_xor_sync(~0u, t, o);
    if ((c & 31) == 0) red[c >> 5] = t;
    __syncthreads();
    if (c == 0) {
        float z = __bfloat162float(b_wide[0]) + __bfloat162float(b2[0]);
        for (int i = 0; i < NH / 32; i++) z += red[i];
        for (int i = 0; i < NW; i++) z = fmaf(__bfloat162float(x_wide[b * NW + i]), __bfloat162float(w_wide[i]), z);
        out[b] = __float2bfloat16(1.f / (1.f + __expf(-z)));
    }
}

typedef CUresult (*EncodeFn)(CUtensorMap*, CUtensorMapDataType, cuuint32_t, void*, const cuuint64_t*, const cuuint64_t*,
                             const cuuint32_t*, const cuuint32_t*, CUtensorMapInterleave, CUtensorMapSwizzle,
                             CUtensorMapL2promotion, CUtensorMapFloatOOBfill);
}

extern "C" void kernel_launch(void* const* d_in, const int* in_sizes, int n_in, void* d_out, int out_size) {
    (void)in_sizes; (void)n_in; (void)out_size;
    static EncodeFn enc = nullptr;
    static Scratch* scratch = nullptr;
    static int mode = 0;
    if (mode == 0) {
        void* fn = nullptr;
        cudaDriverEntryPointQueryResult qr;
        cudaGetDriverEntryPoint("cuTensorMapEncodeTiled", &fn, cudaEnableDefault, &qr);
        enc = (EncodeFn)fn;
        cudaGetSymbolAddress((void**)&scratch, g_scratch);
        cudaFuncSetAttribute(wide_deep_kernel, cudaFuncAttributeMaxDynamicSharedMemorySize, SMEM_BYTES);
        cudaLaunchConfig_t cfg = {};
        cfg.gridDim = dim3(128);
        cfg.blockDim = dim3(NTHREADS);
        cfg.dynamicSmemBytes = SMEM_BYTES;
        cudaLaunchAttribute at;
        at.id = cudaLaunchAttributeClusterDimension;
        at.val.clusterDim.x = 2; at.val.clusterDim.y = 1; at.val.clusterDim.z = 1;
        cfg.attrs = &at;
        cfg.numAttrs = 1;
        int clusters = 0;
        const cudaError_t e = cudaOccupancyMaxActiveClusters(&clusters, wide_deep_kernel, &cfg);
        mode = (enc && e == cudaSuccess && clusters >= 64) ? 1 : 2;
        (void)cudaGetLastError();
    }
    if (mode == 2) {
        wide_deep_fallback<<<NB, NH>>>((const int*)d_in[0], (const __nv_bfloat16*)d_in[1], (const __nv_bfloat16*)d_in[2],
                                       (const __nv_bfloat16*)d_in[3], (const __nv_bfloat16*)d_in[4], (const __nv_bfloat16*)d_in[5],
                                       (const __nv_bfloat16*)d_in[6], (const __nv_bfloat16*)d_in[7], (const __nv_bfloat16*)d_in[8],
                                       (__nv_bfloat16*)d_out);
        return;
    }
    CUtensorMap tmW, tmT;
    {
        cuuint64_t gd[3] = {NH, ND, NF};
        cuuint64_t gs[2] = {NH * 2, (cuuint64_t)NH * 2 * ND};
        cuuint32_t bd[3] = {8, 16, 13};
        cuuint32_t es[3] = {1, 1, 1};
        enc(&tmW, CU_TENSOR_MAP_DATA_TYPE_BFLOAT16, 3, d_in[5], gd, gs, bd, es, CU_TENSOR_MAP_INTERLEAVE_NONE,
            CU_TENSOR_MAP_SWIZZLE_NONE, CU_TENSOR_MAP_L2_PROMOTION_L2_128B, CU_TENSOR_MAP_FLOAT_OOB_FILL_NONE);
    }
    {
        cuuint64_t gd[2] = {ND, NV};
        cuuint64_t gs[1] = {ND * 2};
        cuuint32_t bd[2] = {64, 256};
        cuuint32_t es[2] = {1, 1};
        enc(&tmT, CU_TENSOR_MAP_DATA_TYPE_BFLOAT16, 2, d_in[1], gd, gs, bd, es, CU_TENSOR_MAP_INTERLEAVE_NONE,
            CU_TENSOR_MAP_SWIZZLE_128B, CU_TENSOR_MAP_L2_PROMOTION_L2_128B, CU_TENSOR_MAP_FLOAT_OOB_FILL_NONE);
    }
    wide_deep_kernel<<<128, NTHREADS, SMEM_BYTES>>>(
        scratch, (const int*)d_in[0], 1.0f, tmW, tmT, (const __nv_bfloat16*)d_in[2], (const __nv_bfloat16*)d_in[3],
        (const __nv_bfloat16*)d_in[4], (const __nv_bfloat16*)d_in[6], (const __nv_bfloat16*)d_in[7],
        (const __nv_bfloat16*)d_in[8], (__nv_bfloat16*)d_out);
}
```
